```python
import torch

def _softmax(x, axis=-1):
    return torch.softmax(x, dim=axis)
def _gelu(x):
    return torch.nn.functional.gelu(x, approximate="tanh")
def _silu(x):
    return torch.nn.functional.silu(x)
def _sigmoid(x):
    return torch.sigmoid(x)
def _layernorm(x, axis=-1, eps=1e-5):
    m = x.mean(dim=axis, keepdim=True)
    v = x.var(dim=axis, keepdim=True, unbiased=False)
    return (x - m) / torch.sqrt(v + eps)
def _scatter_add(tgt, idx, src, axis=0):
    return tgt.clone().index_add_(axis, idx, src)
def _segment_sum(src, seg, n):
    out = torch.zeros((n,) + src.shape[1:], dtype=src.dtype)
    return out.index_add_(0, seg, src)
def _pad(x, pw):
    flat = tuple(v for pair in reversed(pw) for v in pair)
    return torch.nn.functional.pad(x, flat)

kernel_name = 'standalone__standard_2d_1d_3d_conv__vision'

def setup_inputs():

    _w = (lambda a: (lambda t: t.to(torch.bfloat16) if t.is_floating_point() else t)(torch.as_tensor(a)))
    H = W = 384
    C = 96
    K = 3
    return {
        "x": _w((lambda *s: torch.randn(*s, dtype=torch.bfloat16) * 0.05)(1, H, W, C)),
        "w": _w((lambda *s: torch.randn(*s, dtype=torch.bfloat16) * 0.05)(K, K, C, C)),
        "b": _w((lambda *s: torch.randn(*s, dtype=torch.bfloat16) * 0.05)(C)),
    }

def reference(x, w, b):
    B, H, W, Cin = x.shape
    K = w.shape[0]
    pl = (K - 1) // 2
    pr = K // 2
    xp = _pad(x, ((0, 0), (pl, pr), (pl, pr), (0, 0)))
    out = sum(
        torch.einsum('bhwc,cd->bhwd', xp[:, i:i+H, j:j+W, :], w[i, j])
        for i in range(K) for j in range(K)
    )
    return out + b[None, None, None, :]
```

```cpp
#include <cuda_runtime.h>
#include <cuda_bf16.h>
#include <cuda.h>
#include <stdint.h>

#define U_FIRST 4
#define TS_STEP 0
#define SKEW_G1 0
#define TR_WARP 0
#define PRE_WARPS 3
#define PIN23 0
#define SKEW 0
#define SKEW_T 4

namespace {

constexpr int IMG = 384;
constexpr int CH = 96;
constexpr int PIECE = 3072;
constexpr int GROUP = 12 * PIECE;
constexpr int NSLOT = 4;
constexpr int PLANE = 5760;
constexpr int STAGE = 2 * PLANE;
constexpr int NSTAGE = 2;
constexpr int ROWBUF = 3072;
constexpr int OFF_OUT = NSLOT * GROUP;
constexpr int OFF_IN = OFF_OUT + 12 * ROWBUF;
constexpr int OFF_BIAS = OFF_IN + 2 * NSTAGE * STAGE;
constexpr int OFF_BAR = OFF_BIAS + 1536;
constexpr int OFF_FULL = OFF_BAR;
constexpr int OFF_UFULL = OFF_BAR + 32;
constexpr int OFF_DRAIN = OFF_BAR + 96;
constexpr int OFF_EMPTY = OFF_BAR + 112;
constexpr int OFF_UREL = OFF_BAR + 144;
constexpr int OFF_END = OFF_BAR + 176;
constexpr int SMEM_BYTES = OFF_END;
constexpr uint32_t SB = 0x400;
constexpr uint32_t DLO = (SB >> 4) | ((128 >> 4) << 16);
constexpr int HALF = GROUP / 2;
constexpr int NCTA = 132;

__device__ uint4 g_U[6 * GROUP / 16];

struct Maps { CUtensorMap in, pf, out; };

__device__ __forceinline__ void wg_fence() { asm volatile("wgmma.fence.sync.aligned;\n" ::: "memory"); }
__device__ __forceinline__ void wg_commit() { asm volatile("wgmma.commit_group.sync.aligned;\n" ::: "memory"); }
template <int N> __device__ __forceinline__ void wg_wait() { asm volatile("wgmma.wait_group.sync.aligned %0;\n" ::"n"(N) : "memory"); }

__device__ __forceinline__ uint32_t bsub(uint32_t a, uint32_t b) {
  uint32_t r; asm("sub.rn.bf16x2 %0, %1, %2;\n" : "=r"(r) : "r"(a), "r"(b)); return r;
}
__device__ __forceinline__ uint32_t badd(uint32_t a, uint32_t b) {
  uint32_t r; asm("add.rn.bf16x2 %0, %1, %2;\n" : "=r"(r) : "r"(a), "r"(b)); return r;
}
__device__ __forceinline__ uint32_t pack2(float lo, float hi) {
  uint32_t r; asm("cvt.rn.bf16x2.f32 %0, %1, %2;\n" : "=r"(r) : "f"(hi), "f"(lo)); return r;
}
__device__ __forceinline__ void mbar_init(uint32_t bar, uint32_t cnt) {
  asm volatile("mbarrier.init.shared::cta.b64 [%0], %1;\n" ::"r"(bar), "r"(cnt) : "memory");
}
__device__ __forceinline__ void mbar_wait(uint32_t bar, uint32_t parity) {
  asm volatile(
      "{\n"
      ".reg .pred p;\n"
      ".reg .u32 n;\n"
      "mov.u32 n, 0;\n"
      "LW%=:\n"
      "mbarrier.try_wait.parity.shared::cta.b64 p, [%0], %1;\n"
      "@p bra LD%=;\n"
      "add.u32 n, n, 1;\n"
      "setp.lt.u32 p, n, 4000000;\n"
      "@p bra LW%=;\n"
      "trap;\n"
      "LD%=:\n"
      "}\n" ::"r"(bar), "r"(parity) : "memory");
}
template <int N> __device__ __forceinline__ void bulk_wait_read() {
  asm volatile("cp.async.bulk.wait_group.read %0;\n" ::"n"(N) : "memory");
}
__device__ __forceinline__ uint32_t bfma(uint32_t a, uint32_t b, uint32_t c) {
  uint32_t r; asm("fma.rn.bf16x2 %0, %1, %2, %3;\n" : "=r"(r) : "r"(a), "r"(b), "r"(c)); return r;
}

template <int SCALE_D, int TB = 1>
__device__ __forceinline__ void wgmma96(float* d, uint32_t a0, uint32_t a1, uint32_t a2, uint32_t a3, uint64_t db) {
  asm volatile(
      "wgmma.mma_async.sync.aligned.m64n96k16.f32.bf16.bf16 "
      "{%0, %1, %2, %3, %4, %5, %6, %7, %8, %9, %10, %11, %12, %13, %14, %15, %16, %17, %18, %19, %20, %21, %22, %23, "
      "%24, %25, %26, %27, %28, %29, %30, %31, %32, %33, %34, %35, %36, %37, %38, %39, %40, %41, %42, %43, %44, %45, %46, %47}, "
      "{%48, %49, %50, %51}, %52, %53, 1, 1, %54;\n"
      : "+f"(d[0]), "+f"(d[1]), "+f"(d[2]), "+f"(d[3]), "+f"(d[4]), "+f"(d[5]), "+f"(d[6]), "+f"(d[7]), "+f"(d[8]), "+f"(d[9]),
        "+f"(d[10]), "+f"(d[11]), "+f"(d[12]), "+f"(d[13]), "+f"(d[14]), "+f"(d[15]), "+f"(d[16]), "+f"(d[17]), "+f"(d[18]),
        "+f"(d[19]), "+f"(d[20]), "+f"(d[21]), "+f"(d[22]), "+f"(d[23]), "+f"(d[24]), "+f"(d[25]), "+f"(d[26]), "+f"(d[27]),
        "+f"(d[28]), "+f"(d[29]), "+f"(d[30]), "+f"(d[31]), "+f"(d[32]), "+f"(d[33]), "+f"(d[34]), "+f"(d[35]), "+f"(d[36]),
        "+f"(d[37]), "+f"(d[38]), "+f"(d[39]), "+f"(d[40]), "+f"(d[41]), "+f"(d[42]), "+f"(d[43]), "+f"(d[44]), "+f"(d[45]),
        "+f"(d[46]), "+f"(d[47])
      : "r"(a0), "r"(a1), "r"(a2), "r"(a3), "l"(db), "n"(SCALE_D), "n"(TB));
}

__device__ __forceinline__ uint64_t bdesc(uint32_t lo) {
  uint64_t d;
  asm("mov.b64 %0, {%1, %2};\n" : "=l"(d) : "r"(lo), "r"(256 >> 4));
  return d;
}

template <int N> __device__ __forceinline__ void fence_regs(float* d) {
#pragma unroll
  for (int i = 0; i < N; i++) asm volatile("" : "+f"(d[i])::"memory");
}

#define TS(i)
#define WAITD(id, bar, par) mbar_wait(bar, par)

struct WItem { uint4 g[3]; };
__device__ __forceinline__ void witem_load(WItem& t, const __nv_bfloat16* __restrict__ w, int item, int lane) {
  const int q = item % 3, kw = (item / 3) % 3, kg = item / 9;
  const uint4* p = (const uint4*)(w + (kw * CH + kg * 8 + (lane & 7)) * CH + q * 32 + (lane >> 3) * 8);
#pragma unroll
  for (int i = 0; i < 3; i++) t.g[i] = __ldg(p + i * (3 * CH * CH / 8));
}
__device__ __forceinline__ void witem_store(const WItem& t, char* dst, int item, int lane) {
  const int q = item % 3, kw = (item / 3) % 3, kg = item / 9;
  const uint32_t* a = (const uint32_t*)&t.g[0];
  const uint32_t* b = (const uint32_t*)&t.g[1];
  const uint32_t* c = (const uint32_t*)&t.g[2];
  uint32_t u1[4], u2[4];
#pragma unroll
  for (int j = 0; j < 4; j++) {
    const float sl = __uint_as_float(a[j] << 16) + __uint_as_float(c[j] << 16);
    const float sh = __uint_as_float(a[j] & 0xffff0000u) + __uint_as_float(c[j] & 0xffff0000u);
    const float bl = __uint_as_float(b[j] << 16), bh = __uint_as_float(b[j] & 0xffff0000u);
    u1[j] = pack2(0.5f * (sl + bl), 0.5f * (sh + bh));
    u2[j] = pack2(0.5f * (sl - bl), 0.5f * (sh - bh));
  }
  dst += (kg >> 1) * GROUP + kw * PIECE + (q * 4 + (lane >> 3)) * 256 + (kg & 1) * 128 + (lane & 7) * 16;
  *(uint4*)(dst) = t.g[0];
  *(uint4*)(dst + 3 * PIECE) = make_uint4(u1[0], u1[1], u1[2], u1[3]);
  *(uint4*)(dst + 6 * PIECE) = make_uint4(u2[0], u2[1], u2[2], u2[3]);
  *(uint4*)(dst + 9 * PIECE) = t.g[2];
}
__global__ void __launch_bounds__(32 * PRE_WARPS) wino_weights_kernel(const __nv_bfloat16* __restrict__ w, char* gu) {
  asm volatile("griddepcontrol.launch_dependents;\n" ::: "memory");
  WItem t;
  const int item = blockIdx.x * PRE_WARPS + (threadIdx.x >> 5);
  witem_load(t, w, item, threadIdx.x & 31);
  witem_store(t, gu, item, threadIdx.x & 31);
}

struct Ctx {
  uint32_t wg;
  uint32_t warp;
  uint32_t zero;
  const char* gu;
  uint64_t m_in, m_pf, m_out;
  int xa, ya, xb, yb;
  uint32_t role;
};

__device__ __forceinline__ void unit_xy(const Ctx& c, int step, int& x0, int& y0) {
  x0 = (step < 4) ? c.xa : c.xb;
  y0 = (step < 4) ? c.ya + 88 * step : c.yb;
}

__device__ __forceinline__ void issue_stage(uint64_t tm, uint32_t wg, int stage, int pair, int x0, int y0) {
  const uint32_t bar = SB + OFF_FULL + (wg * NSTAGE + stage) * 8;
  const uint32_t dst = SB + OFF_IN + (wg * NSTAGE + stage) * STAGE;
  asm volatile(
      "{\n.reg .pred p;\n"
      "elect.sync _|p, 0xffffffff;\n"
      "@p mbarrier.arrive.expect_tx.shared::cta.b64 _, [%2], %9;\n"
      "@p cp.async.bulk.tensor.4d.shared::cluster.global.mbarrier::complete_tx::bytes [%0], [%1, {%3, %7, %4, %6}], [%2];\n"
      "@p cp.async.bulk.tensor.4d.shared::cluster.global.mbarrier::complete_tx::bytes [%0 + %10], [%1, {%3, %8, %5, %6}], [%2];\n"
      "}\n" ::"r"(dst), "l"(tm), "r"(bar), "r"(pair * 32), "r"((x0 >> 1) - 1), "r"(x0 >> 1), "r"(y0 - 1), "r"(1), "r"(0),
      "n"(STAGE), "n"(PLANE) : "memory");
}
__device__ __forceinline__ void u_reload(const char* gu, int from, int h) {
  const int hs = (from & 3) * 2 + h;
  asm volatile(
      "{\n.reg .pred p;\n"
      "elect.sync _|p, 0xffffffff;\n"
      "@p mbarrier.arrive.expect_tx.shared::cta.b64 _, [%2], %3;\n"
      "@p cp.async.bulk.shared::cluster.global.mbarrier::complete_tx::bytes [%0], [%1], %3, [%2];\n"
      "}\n" ::"r"(SB + hs * HALF), "l"(gu + ((from ^ 4) * 2 + h) * HALF), "r"(SB + OFF_UFULL + hs * 8), "n"(HALF) : "memory");
}
__device__ __forceinline__ void e_prefetch3(uint64_t tm, int c1, int c2) {
  asm volatile("{\n.reg .pred p;\nelect.sync _|p, 0xffffffff;\n"
               "@p cp.async.bulk.prefetch.tensor.3d.L2.global [%0, {%1, %2, %3}];\n}\n" ::"l"(tm), "r"(0), "r"(c1), "r"(c2) : "memory");
}
__device__ __forceinline__ void e_store3(uint64_t tm, uint32_t src, int c1, int c2) {
  asm volatile("{\n.reg .pred p;\nelect.sync _|p, 0xffffffff;\n"
               "@p cp.async.bulk.tensor.3d.global.shared::cta.bulk_group [%0, {%2, %3, %4}], [%1];\n"
               "cp.async.bulk.commit_group;\n}\n" ::"l"(tm), "r"(src), "r"(0), "r"(c1), "r"(c2) : "memory");
}
__device__ __forceinline__ void e_arrive(uint32_t bar) {
  asm volatile("{\n.reg .pred p;\nelect.sync _|p, 0xffffffff;\n@p mbarrier.arrive.shared::cta.b64 _, [%0];\n}\n" ::"r"(bar) : "memory");
}
__device__ __forceinline__ uint32_t mbar_try(uint32_t bar, uint32_t parity) {
  uint32_t ok;
  asm volatile("{\n.reg .pred p;\nmbarrier.test_wait.parity.shared::cta.b64 p, [%1], %2;\nselp.u32 %0, 1, 0, p;\n}\n"
               : "=r"(ok) : "r"(bar), "r"(parity) : "memory");
  return ok;
}

struct Addr { uint32_t e[4]; };
__device__ __forceinline__ void addr_flip(Addr& ad, uint32_t k32) {
  asm volatile("xor.b32 %0, %0, %4;\nxor.b32 %1, %1, %4;\nxor.b32 %2, %2, %4;\nxor.b32 %3, %3, %4;\n"
               : "+r"(ad.e[0]), "+r"(ad.e[1]), "+r"(ad.e[2]), "+r"(ad.e[3]) : "r"(k32));
}
template <int IMM> __device__ __forceinline__ void ldsm4(uint32_t* r, uint32_t a) {
  asm volatile("ldmatrix.sync.aligned.m8n8.x4.shared.b16 {%0,%1,%2,%3}, [%4 + %5];\n"
               : "=r"(r[0]), "=r"(r[1]), "=r"(r[2]), "=r"(r[3]) : "r"(a), "n"(IMM));
}
template <int IMM> __device__ __forceinline__ void ldsm4_tied(uint32_t* r, uint32_t a, uint32_t zero) {
  asm volatile("{\n.reg .pred p;\nsetp.ne.u32 p, %6, 0;\n@!p ldmatrix.sync.aligned.m8n8.x4.shared.b16 {%0,%1,%2,%3}, [%4 + %5];\n}\n"
               : "+r"(r[0]), "+r"(r[1]), "+r"(r[2]), "+r"(r[3]) : "r"(a), "n"(IMM), "r"(zero));
}
template <int RHO, int STG> __device__ __forceinline__ void load_row(uint32_t* d, const Addr& ad, uint32_t k32 = 32) {
  ldsm4<RHO * 576 + STG * STAGE>(d, ad.e[RHO]);
  ldsm4<RHO * 576 + 64 + STG * STAGE>(d + 4, RHO == 3 ? ad.e[0] ^ k32 : ad.e[(RHO + 1) & 3]);
}
template <int STG> __device__ __forceinline__ void load_row1_tied(uint32_t* d, const Addr& ad, uint32_t zero) {
  ldsm4_tied<576 + STG * STAGE>(d, ad.e[1], zero);
  ldsm4_tied<640 + STG * STAGE>(d + 4, ad.e[2], zero);
}
__device__ __forceinline__ uint32_t lane_id() { uint32_t l; asm volatile("mov.u32 %0, %%laneid;\n" : "=r"(l)); return l; }

template <int SCALE_D>
__device__ __forceinline__ void mma_group(float* acc, const uint32_t* v, uint32_t baddr) {
  wgmma96<SCALE_D>(acc, v[0], v[1], v[2], v[3], bdesc(baddr));
  wgmma96<1>(acc, v[4], v[5], v[6], v[7], bdesc(baddr + (2 * PIECE >> 4)));
  wgmma96<1>(acc, v[1], v[4], v[3], v[6], bdesc(baddr + (PIECE >> 4)));
  wg_commit();
}
template <uint32_t K> __device__ __forceinline__ uint32_t pinned_const(uint32_t x, uint32_t zero) {
  uint32_t m;
  asm("{\n.reg .pred p;\nsetp.ne.u32 p, %2, 0;\nselp.b32 %0, %1, %3, p;\n}\n" : "=r"(m) : "r"(x), "r"(zero), "n"(K));
  return m;
}
template <bool NEG>
__device__ __forceinline__ uint32_t pin_one(float& done, uint32_t zero) {
  asm volatile("" : "+f"(done)::"memory");
  return pinned_const<NEG ? 0xBF80BF80u : 0x3F803F80u>(__float_as_uint(done), zero);
}
__device__ __forceinline__ void vfma(uint32_t* v, const uint32_t* a, uint32_t m, const uint32_t* b) {
#pragma unroll
  for (int i = 0; i < 8; i++) v[i] = bfma(a[i], m, b[i]);
}
__device__ __forceinline__ void vsub(uint32_t* v, const uint32_t* a, const uint32_t* b) {
#pragma unroll
  for (int i = 0; i < 8; i++) v[i] = bsub(a[i], b[i]);
}
__device__ __forceinline__ void vadd(uint32_t* v, const uint32_t* a, const uint32_t* b) {
#pragma unroll
  for (int i = 0; i < 8; i++) v[i] = badd(a[i], b[i]);
}
__device__ __forceinline__ uint32_t bias_frag(uint32_t lane) { return (lane & 3) ? 0u : 0x3F00u; }
__device__ __forceinline__ void mma_bias(float* acc, uint32_t a, const Ctx& c) {
  uint64_t d;
  asm("mov.b64 %0, {%1, %2};\n" : "=l"(d) : "r"((SB + OFF_BIAS) >> 4), "r"(128 >> 4));
  wgmma96<0, 0>(acc, a, a, a, a, d);
}

template <int ROW> __device__ __forceinline__ uint32_t out_buf(const Ctx& c) {
  return SB + OFF_OUT + (c.warp * 3 + (ROW == 0 ? 2 * c.wg : 1 - c.wg)) * ROWBUF;
}
template <int ROW>
__device__ __forceinline__ void pack_row(uint32_t (&r)[24], float (&acc)[4][48]) {
#pragma unroll
  for (int k = 0; k < 24; k++) {
    const int i = 4 * (k % 12) + 2 * (k / 12);
    if (ROW == 0) {
      r[k] = pack2(acc[0][i] + (acc[1][i] + acc[2][i]), acc[0][i + 1] + (acc[1][i + 1] + acc[2][i + 1]));
      acc[1][i] -= acc[2][i]; acc[1][i + 1] -= acc[2][i + 1];
    } else {
      r[k] = pack2(acc[1][i] - acc[3][i], acc[1][i + 1] - acc[3][i + 1]);
    }
  }
}
template <int ROW>
__device__ __forceinline__ void stage_row(const uint32_t (&r)[24], const Ctx& c, uint32_t lane) {
  const uint32_t l3 = 48 * (lane & 7);
  const uint32_t p0 = out_buf<ROW>(c) + 8 * l3 + 2 * (lane & 24);
#pragma unroll
  for (int L = 0; L < 3; L++) {
    const uint32_t a = p0 ^ ((l3 + 16 * L) & 0x70);
    asm volatile("stmatrix.sync.aligned.m8n8.x4.shared.b16 [%0], {%1,%2,%3,%4};\n" ::"r"(a + 128 * L), "r"(r[8 * L]),
                 "r"(r[8 * L + 1]), "r"(r[8 * L + 2]), "r"(r[8 * L + 3]) : "memory");
    asm volatile("stmatrix.sync.aligned.m8n8.x4.shared.b16 [%0], {%1,%2,%3,%4};\n" ::"r"((a ^ 64) + 128 * L), "r"(r[8 * L + 4]),
                 "r"(r[8 * L + 5]), "r"(r[8 * L + 6]), "r"(r[8 * L + 7]) : "memory");
  }
}
__device__ __forceinline__ void proxy_fence() { asm volatile("fence.proxy.async.shared::cta;\n" ::: "memory"); }
__device__ __forceinline__ void flush_shared(const Ctx& c, int x0, int y0) {
  e_store3(c.m_out, SB + OFF_OUT + c.warp * 3 * ROWBUF, (x0 * 3) >> 1, y0 + 2 * c.warp + c.wg);
}
__device__ __forceinline__ void flush_private(const Ctx& c, int x0, int y0) {
  e_store3(c.m_out, SB + OFF_OUT + (c.warp * 3 + 1 + c.wg) * ROWBUF, (x0 * 3) >> 1, y0 + 2 * c.warp + 1 - c.wg);
}

enum : uint32_t {
  B_REFILL = 1u << 0,
  B_UREL = 1u << 3,
  B_ULOAD = 1u << 4,
  B_ST = 1u << 5,
  B_PF = 1u << 13,
  B_PF0 = 1u << 19,
  B_FIRST = 1u << 20,
  B_DRAIN0 = 1u << 21,
  B_DRAIN1 = 1u << 22,
  B_WAIT1 = 1u << 23,
  B_NEXT = 1u << 24,
  B_SKEW_ARRIVE = 1u << 25,
};
__device__ __forceinline__ uint32_t role_mask(uint32_t wg, uint32_t warp) {
  uint32_t m = B_NEXT | B_FIRST;
  if (warp == 0) m |= 7u * B_REFILL;
  if (warp == 3) m |= wg ? B_ULOAD : B_UREL;
  if (wg == 0) m |= B_DRAIN0 | B_WAIT1 | B_SKEW_ARRIVE;
  else m |= B_DRAIN1 | (B_ST << (warp ^ 1));
  m |= (B_ST << 4) << (warp ^ 1);
  if (warp == 2) m |= (63u * B_PF) | B_PF0;
  return m;
}
__device__ __forceinline__ uint32_t step_mask(int step, int nsteps) {
  uint32_t m = ~0u;
  if (step == 0) m &= ~(B_DRAIN0 | B_DRAIN1 | (255u * B_ST) | B_WAIT1);
  else m &= ~(B_PF0 | B_FIRST);
  if (step + 1 >= nsteps) m &= ~((6u * B_REFILL) | (7u * B_PF) | B_NEXT);
  if (step + 2 >= nsteps) m &= ~(56u * B_PF);
  if (step == 4) m &= ~B_SKEW_ARRIVE;
  return m;
}
struct Unit { int step, x0, y0, xn, yn, yp, x2, y2; uint32_t ctl; };
#define CTL(b) (u.ctl & (b))
#define TR(i)

template <int DIR, int T, int EV>
__device__ __forceinline__ void duty_u(const Ctx& c, const Unit& u) {
  const int step = u.step; (void)step;
  if (CTL(B_UREL)) e_arrive(SB + OFF_UREL + EV * 8);
  if (CTL(B_ULOAD)) { WAITD(1, SB + OFF_UREL + EV * 8, DIR); u_reload(c.gu, DIR ? 5 - (EV >> 1) : (EV >> 1), EV & 1); }
}
template <int DIR, int T>
__device__ __forceinline__ void duty_pf(const Ctx& c, const Unit& u) {
  constexpr int j = (T + 3) % 6;
  if (CTL(B_PF << T)) {
    if (T >= 3) e_prefetch3(c.m_pf, ((u.x2 * 3) >> 1) + 12 * (j & 1), u.y2 + 3 * (j >> 1));
    else {
      if (DIR == 0) { if (CTL(B_PF0)) e_prefetch3(c.m_pf, ((u.xn * 3) >> 1) + 12 * (T & 1), u.yn + 3 * (T >> 1)); }
      e_prefetch3(c.m_pf, ((u.xn * 3) >> 1) + 12 * (j & 1), u.yn + 3 * (j >> 1));
    }
  }
}
template <int SITE>
__device__ __forceinline__ void duty_st(const Ctx& c, const Unit& u) {
  if (CTL(B_ST << SITE)) { if (SITE < 4) flush_shared(c, c.xa, u.yp); else flush_private(c, c.xa, u.yp); }
}

template <int DIR, int T>
__device__ __forceinline__ void do_chunk(float (&acc)[4][48], uint32_t (&d0)[8], uint32_t (&d1)[8], uint32_t (&d2)[8],
                                         uint32_t (&d3)[8], uint32_t (&v3)[8], uint32_t& ok, Addr& ad, const Ctx& c, const Unit& u) {
  constexpr int chunk = DIR ? 5 - T : T;
  constexpr int slot = chunk & 3;
  constexpr int kp = 3 * DIR + (T >> 1);
  constexpr int stage = kp & 1;
  constexpr int nchunk = (T == 5) ? chunk : (DIR ? chunk - 1 : chunk + 1);
  constexpr int nslot = nchunk & 3;
  constexpr int kp1 = 3 * DIR + ((T + 1) >> 1);
  constexpr int nstage = kp1 & 1;
  constexpr int ph = (chunk & 1) ^ stage, nph = (nchunk & 1) ^ nstage;
  constexpr uint32_t ub = DLO + (slot * GROUP >> 4);
  constexpr uint32_t nub = DLO + (nslot * GROUP >> 4);
  const int step = u.step;
  const uint32_t pbit = (step >> 1) & 1;
  const uint32_t wgbar = SB + c.wg * NSTAGE * 8;
  const uint32_t emptybar = wgbar + OFF_EMPTY + stage * 8;
  constexpr uint32_t h2bar = SB + OFF_UFULL + (slot * 2 + 1) * 8;
  constexpr uint32_t h1bar = SB + OFF_UFULL + (nslot * 2) * 8;
  uint32_t v[8], v1[8];

  if (T == 0) {
    TR(0);
    vsub(v, d0, d2);
    wg_fence();
    load_row1_tied<nstage>(d1, ad, c.zero);
    load_row<3, nstage>(d3, ad, 32 + (T + 6 * DIR + 20) * c.zero);
    e_arrive(emptybar);
    mma_group<0>(acc[3], v3, ub + (9 * PIECE >> 4));
    mma_group<1>(acc[0], v, nub);
    TR(1);
    proxy_fence();
    if (CTL(B_UREL | B_ULOAD | B_PF | B_ST)) {
      duty_u<DIR, T, 0>(c, u);
      duty_pf<DIR, T>(c, u);
      duty_st<0>(c, u);
    }
    TR(2); TR(3);
  } else {
    wg_wait<1>();
    vfma(v1, d1, pin_one<false>(acc[3][0], c.zero), d2);
    wg_fence();
    mma_group<1>(acc[1], v1, ub + (3 * PIECE >> 4));
    TR(0);
    {
      constexpr int P = T >> 1;
      constexpr int site = T == 1 ? 1 : T == 2 ? 3 : T == 3 ? 4 : 6;
      constexpr uint32_t mask = (B_PF << T) | ((T & 1) ? B_REFILL << P : 0u) | (T <= 2 ? B_UREL | B_ULOAD : 0u) |
                                (T <= 4 ? B_ST << site : 0u) | (T <= 3 && DIR == 0 ? B_FIRST : 0u) | (T == 1 ? B_DRAIN0 : 0u) |
                                (T == 3 ? B_DRAIN1 : 0u) | (T == 5 ? B_WAIT1 : 0u);
      if (!ok || CTL(mask)) {
        if (T & 1) {
          if (CTL(B_REFILL << P)) {
            WAITD(0, emptybar, pbit ^ ((kp >> 1) & 1));
            issue_stage(c.m_in, c.wg, stage, (P == 2) ? 1 : (DIR ? 0 : 2), P == 0 ? u.x0 : u.xn, P == 0 ? u.y0 : u.yn);
          }
        }
        if (T <= 2) duty_u<DIR, T, (T == 1 ? 1 : 3)>(c, u);
        duty_pf<DIR, T>(c, u);
        if (T == 1) { if (CTL(B_DRAIN0)) { bulk_wait_read<0>(); e_arrive(SB + OFF_DRAIN); } }
        if (T == 3) { if (CTL(B_DRAIN1)) { bulk_wait_read<0>(); e_arrive(SB + OFF_DRAIN + 8); } }
        if (T <= 4) duty_st<site>(c, u);
        if (T == 5) { if (CTL(B_WAIT1)) WAITD(4, SB + OFF_DRAIN + 8, DIR ^ 1); }
        if (T <= 3 && DIR == 0) {
          if (CTL(B_FIRST)) { WAITD(3, h2bar, 0); if (T < 3) WAITD(5, h1bar, 0); }
        }
        if (!ok) {
          if (T & 1) { if (T < 5 || CTL(B_NEXT)) WAITD(2, wgbar + OFF_FULL + nstage * 8, pbit ^ ((kp1 >> 1) & 1)); }
          if (T >= 4) WAITD(3, h2bar, DIR ^ 1);
        }
      }
    }
    TR(1);
    wg_wait<1>();
    if (T == 3 || T == 4) ok = mbar_try(h1bar, DIR ^ 1);
    if (PIN23) {
      const uint32_t m = pin_one<true>(acc[0][0], c.zero);
      vfma(v, d1, m, d2);
      vfma(v3, d3, m, d1);
    } else {
      vsub(v, d2, d1);
      vsub(v3, d1, d3);
    }
    if (ph != nph) addr_flip(ad, 32 + (T + 6 * DIR + 1) * c.zero);
    wg_fence();
    load_row<2, nstage>(d2, ad);
    load_row<0, nstage>(d0, ad);
    mma_group<1>(acc[2], v, ub + (6 * PIECE >> 4));
    mma_group<1>(acc[3], v3, ub + (9 * PIECE >> 4));
    if (T == 5) bulk_wait_read<0>();
    TR(2);
    wg_wait<2>();
    if (T == 1) {
      if (CTL(B_UREL | B_ULOAD | (B_ST << 2))) { duty_u<DIR, T, 2>(c, u); duty_st<2>(c, u); }
    }
    if (T == 3 || T == 4) {
      constexpr int site = T == 3 ? 5 : 7;
      if (!ok || CTL(B_ST << site)) {
        duty_st<site>(c, u);
        if (!ok) WAITD(5, h1bar, DIR ^ 1);
      }
    }
    load_row1_tied<nstage>(v1, ad, c.zero);
#pragma unroll
    for (int i = 0; i < 8; i++) d1[i] = v1[i];
    TR(3);
  }
  if (step == TS_STEP) TS(5 + T);
  if (T < 5) {
    if (T > 0) {
      wg_wait<1>();
      vfma(v, d2, pin_one<true>(acc[2][0], c.zero), d0);
      wg_fence();
      load_row<3, nstage>(d3, ad, 32 + (T + 6 * DIR + 20) * c.zero);
      if (!(T & 1)) e_arrive(emptybar);
      mma_group<1>(acc[0], v, nub);
    }
    constexpr int N = T + 1;
    constexpr int kp2 = 3 * DIR + ((N + 1) >> 1);
    ok = 1;
    if (N & 1) ok &= mbar_try(wgbar + OFF_FULL + (kp2 & 1) * 8, pbit ^ ((kp2 >> 1) & 1));
    if (N >= 4) ok &= mbar_try(SB + OFF_UFULL + (nslot * 2 + 1) * 8, DIR ^ 1);
    TR(4);
  } else {
    const uint32_t lane = lane_id();
    wg_wait<1>();
    TS(11 + 3 * step);
    fence_regs<48>(acc[0]); fence_regs<48>(acc[1]); fence_regs<48>(acc[2]);
    uint32_t r[24];
    pack_row<0>(r, acc);
    stage_row<0>(r, c, lane + (u.y0 & c.zero));
    wg_wait<0>();
    fence_regs<48>(acc[3]);
    {
      uint32_t v2[8];
      const uint32_t m = pin_one<true>(acc[3][0], c.zero);
      vfma(v, d2, m, d0);
      vfma(v2, d1, m, d2);
      wg_fence();
      load_row<3, nstage>(d3, ad, 32 + (T + 6 * DIR + 20) * c.zero);
      mma_group<0>(acc[0], v, nub);
      mma_group<0>(acc[2], v2, nub + (6 * PIECE >> 4));
    }
    TR(4);
    TS(12 + 3 * step);
    pack_row<1>(r, acc);
    if (c.wg == 0) { proxy_fence(); flush_shared(c, u.x0, u.y0); }
    else WAITD(6, SB + OFF_DRAIN, DIR);
    stage_row<1>(r, c, lane + ((u.y0 + 1) & c.zero));
    wg_wait<1>();
    vfma(v1, d1, pin_one<false>(acc[0][0], c.zero), d2);
    vsub(v3, d1, d3);
    const uint32_t ba = bias_frag(lane + ((u.y0 + 2) & c.zero));
    addr_flip(ad, 32 + (14 + DIR) * c.zero);
    wg_fence();
    load_row<2, nstage>(d2, ad);
    load_row<0, nstage>(d0, ad);
    mma_bias(acc[1], ba, c);
    mma_group<1>(acc[1], v1, nub + (3 * PIECE >> 4));
    wg_wait<0>(); fence_regs<48>(acc[0]); fence_regs<48>(acc[1]); fence_regs<48>(acc[2]);
#pragma unroll
    for (int i = 0; i < 8; i++) d1[i] = v1[i];
    TS(13 + 3 * step);
  }
}

template <int DIR>
__device__ __forceinline__ void do_unit(float (&acc)[4][48], uint32_t (&d0)[8], uint32_t (&d1)[8], uint32_t (&d2)[8], uint32_t (&v3)[8], Addr& ad,
                                        const Ctx& c, int step, int nsteps) {
  Unit u;
  u.step = step;
  u.yp = c.ya + 88 * (step - 1);
  unit_xy(c, step, u.x0, u.y0);
  unit_xy(c, step + 1, u.xn, u.yn);
  unit_xy(c, step + 2, u.x2, u.y2);
  asm volatile("and.b32 %0, %1, %2;\n" : "=r"(u.ctl) : "r"(c.role), "r"(step_mask(step, nsteps)));
  uint32_t ok = 1, d3[8];
  do_chunk<DIR, 0>(acc, d0, d1, d2, d3, v3, ok, ad, c, u);
  do_chunk<DIR, 1>(acc, d0, d1, d2, d3, v3, ok, ad, c, u);
  do_chunk<DIR, 2>(acc, d0, d1, d2, d3, v3, ok, ad, c, u);
  do_chunk<DIR, 3>(acc, d0, d1, d2, d3, v3, ok, ad, c, u);
  do_chunk<DIR, 4>(acc, d0, d1, d2, d3, v3, ok, ad, c, u);
  do_chunk<DIR, 5>(acc, d0, d1, d2, d3, v3, ok, ad, c, u);
}

__global__ void __launch_bounds__(256, 1)
wino_conv_kernel(const __grid_constant__ Maps maps, const __nv_bfloat16* __restrict__ bias, const char* gu, uint32_t zero) {
  extern __shared__ __align__(1024) uint8_t smem[];
  Ctx c;
  const int tid = threadIdx.x;
  if (tid == 32) asm volatile("prefetch.tensormap [%0];\n" ::"l"(&maps.in) : "memory");
  const uint32_t w8 = __shfl_sync(0xffffffffu, tid >> 5, 0);
  const int cta = blockIdx.x;
  const int lane = tid & 31;
  c.wg = w8 >> 2;
  c.warp = w8 & 3;
  c.xa = ((cta % 12) * 2 + c.wg) * 16; c.ya = (cta / 12) * 8;
  if (w8 == 0) {
    if (lane < 2 * NSTAGE) mbar_init(SB + OFF_FULL + lane * 8, 1);
    asm volatile("fence.mbarrier_init.release.cluster;\n" ::: "memory");
    __syncwarp();
    issue_stage((uint64_t)&maps.in, 0, 0, 0, c.xa, c.ya);
    issue_stage((uint64_t)&maps.in, 1, 0, 0, c.xa + 16, c.ya);
  }
  c.role = __shfl_sync(0xffffffffu, role_mask(tid >> 7, (tid >> 5) & 3), 0);
  c.m_in = __shfl_sync(0xffffffffu, (unsigned long long)&maps.in, 0);
  c.m_pf = __shfl_sync(0xffffffffu, (unsigned long long)&maps.pf, 0);
  c.m_out = __shfl_sync(0xffffffffu, (unsigned long long)&maps.out, 0);
  c.zero = zero;
  c.gu = gu;
  const int nsteps = (c.wg == 0 && cta < 96) ? 5 : 4;
  c.xb = (cta % 24) * 16; c.yb = 352 + (cta / 24) * 8;
  TS(0);
  if (w8 == 7) {
    if ((uint32_t)__cvta_generic_to_shared(smem) != SB) __trap();
    if (lane < 18) mbar_init(SB + OFF_UFULL + lane * 8, (lane >= 8 && lane < 14) ? 4 : 1);
    asm volatile("fence.mbarrier_init.release.cluster;\n" ::: "memory");
    asm volatile("bar.arrive 1, 256;\n" ::: "memory");
    asm volatile("griddepcontrol.wait;\n" ::: "memory");
#pragma unroll
    for (int h = 0; h < U_FIRST; h++) u_reload(gu, (h >> 1) ^ 4, h & 1);
    asm volatile("bar.sync 2, 256;\n" ::: "memory");
    issue_stage(c.m_in, 0, 1, 1, c.xa - 16, c.ya);
    issue_stage(c.m_in, 1, 1, 1, c.xa, c.ya);
#pragma unroll
    for (int h = U_FIRST; h < 8; h++) u_reload(gu, (h >> 1) ^ 4, h & 1);
#pragma unroll
    for (int j = 0; j < 4; j++)
      asm volatile("{\n.reg .pred p;\nelect.sync _|p, 0xffffffff;\n"
                   "@p cp.async.bulk.prefetch.tensor.4d.L2.global [%0, {%1, %2, %3, %4}];\n}\n" ::"l"(c.m_in), "r"(64), "r"(j & 1),
                   "r"((c.xa >> 1) - 8 * (j >> 1) - (j & 1)), "r"(c.ya - 1) : "memory");
  } else {
    if (w8 >= 1 && w8 <= 3) {
      *(uint4*)(smem + OFF_BIAS + (tid - 32) * 16) = make_uint4(((const unsigned short*)bias)[tid - 32], 0, 0, 0);
      proxy_fence();
    }
    TS(1);
    asm volatile("bar.arrive 2, 256;\n" ::: "memory");
    asm volatile("bar.sync 1, 256;\n" ::: "memory");
  }
  TS(2);
  Addr ad;
  {
    const int m = lane >> 3, i = lane & 7;
    const uint32_t abase = SB + OFF_IN + c.wg * NSTAGE * STAGE + (m & 1) * PLANE + (18 * c.warp + i) * 64 + (m >> 1) * 16;
#pragma unroll
    for (int s = 0; s < 4; s++) ad.e[s] = abase ^ (((abase >> 3) + 8 * s) & 0x30);
  }

  float acc[4][48];
#pragma unroll
  for (int p = 0; p < 4; p++)
#pragma unroll
    for (int i = 0; i < 48; i++) acc[p][i] = 0.f;
  uint32_t d0[8], d2[8], v1[8], v3[8];
  {
    uint32_t d1[8], d3[8], v0[8], v2[8];
    mbar_wait(SB + OFF_FULL + (c.wg * NSTAGE) * 8, 0);
    TS(3);
    load_row<0, 0>(d0, ad);
    load_row<2, 0>(d2, ad);
    load_row<1, 0>(d1, ad);
    load_row<3, 0>(d3, ad);
    vsub(v0, d0, d2);
    vadd(v1, d1, d2);
    vsub(v2, d2, d1);
    vsub(v3, d1, d3);
    const uint32_t ba = bias_frag(lane);
    addr_flip(ad, 32);
    load_row<0, 0>(d0, ad);
    load_row<2, 0>(d2, ad);
    mbar_wait(SB + OFF_UFULL, 0);
    mbar_wait(SB + OFF_UFULL + 8, 0);
    wg_fence();
    mma_group<0>(acc[0], v0, DLO);
    mma_bias(acc[1], ba, c);
    mma_group<1>(acc[1], v1, DLO + (3 * PIECE >> 4));
    mma_group<0>(acc[2], v2, DLO + (6 * PIECE >> 4));
    mbar_wait(SB + OFF_UFULL + 16, 0);
    TS(4);
    wg_wait<0>(); fence_regs<48>(acc[0]); fence_regs<48>(acc[1]); fence_regs<48>(acc[2]);
  }

  int step = 0;
#pragma unroll 1
  while (true) {
    do_unit<0>(acc, d0, v1, d2, v3, ad, c, step, nsteps);
    if (++step == nsteps) break;
    do_unit<1>(acc, d0, v1, d2, v3, ad, c, step, nsteps);
    if (++step == nsteps) break;
  }
  if (c.wg == 1 && blockIdx.x < 96) {
    if (c.role & B_ULOAD) {
#pragma unroll
      for (int i = 0; i < 4; i++) { mbar_wait(SB + OFF_UREL + i * 8, 0); u_reload(gu, i >> 1, i & 1); }
    }
  }
  {
    int x0, y0;
    unit_xy(c, step - 1, x0, y0);
    proxy_fence();
    if (c.wg) flush_shared(c, x0, y0);
    flush_private(c, x0, y0);
    bulk_wait_read<1>();
    e_arrive(SB + OFF_DRAIN + c.wg * 8);
  }
  bulk_wait_read<0>();
}

typedef CUresult (*EncodeFn)(CUtensorMap*, CUtensorMapDataType, cuuint32_t, void*, const cuuint64_t*, const cuuint64_t*,
                             const cuuint32_t*, const cuuint32_t*, CUtensorMapInterleave, CUtensorMapSwizzle,
                             CUtensorMapL2promotion, CUtensorMapFloatOOBfill);

}

extern "C" void kernel_launch(void* const* d_in, const int* in_sizes, int n_in, void* d_out, int out_size) {
  (void)in_sizes; (void)n_in; (void)out_size;
  const __nv_bfloat16* x = (const __nv_bfloat16*)d_in[0];
  const __nv_bfloat16* w = (const __nv_bfloat16*)d_in[1];
  const __nv_bfloat16* b = (const __nv_bfloat16*)d_in[2];
  __nv_bfloat16* out = (__nv_bfloat16*)d_out;

  static EncodeFn encode = nullptr;
  static void* gu = nullptr;
  if (!encode) {
    cudaGetSymbolAddress(&gu, g_U);
    void* fn = nullptr;
    cudaDriverEntryPointQueryResult qr;
    cudaGetDriverEntryPoint("cuTensorMapEncodeTiled", &fn, cudaEnableDefault, &qr);
    encode = (EncodeFn)fn;
    cudaFuncSetAttribute(wino_conv_kernel, cudaFuncAttributeMaxDynamicSharedMemorySize, SMEM_BYTES);
  }
  Maps maps;
  {
    cuuint64_t dims[4] = {CH, 2, IMG / 2, IMG};
    cuuint64_t strides[3] = {CH * 2, 2 * CH * 2, (cuuint64_t)IMG * CH * 2};
    cuuint32_t box[4] = {32, 1, 9, 10};
    cuuint32_t es[4] = {1, 1, 1, 1};
    encode(&maps.in, CU_TENSOR_MAP_DATA_TYPE_BFLOAT16, 4, (void*)x, dims, strides, box, es, CU_TENSOR_MAP_INTERLEAVE_NONE,
           CU_TENSOR_MAP_SWIZZLE_64B, CU_TENSOR_MAP_L2_PROMOTION_NONE, CU_TENSOR_MAP_FLOAT_OOB_FILL_NONE);
  }
  {
    cuuint64_t dims[3] = {64, IMG * CH / 64, IMG};
    cuuint64_t strides[2] = {128, (cuuint64_t)IMG * CH * 2};
    cuuint32_t box[3] = {64, 12, 3};
    cuuint32_t es[3] = {1, 1, 1};
    encode(&maps.pf, CU_TENSOR_MAP_DATA_TYPE_BFLOAT16, 3, (void*)x, dims, strides, box, es, CU_TENSOR_MAP_INTERLEAVE_NONE,
           CU_TENSOR_MAP_SWIZZLE_NONE, CU_TENSOR_MAP_L2_PROMOTION_NONE, CU_TENSOR_MAP_FLOAT_OOB_FILL_NONE);
  }
  {
    cuuint64_t dims[3] = {64, IMG * CH / 64, IMG};
    cuuint64_t strides[2] = {128, (cuuint64_t)IMG * CH * 2};
    cuuint32_t box[3] = {64, 24, 1};
    cuuint32_t es[3] = {1, 1, 1};
    encode(&maps.out, CU_TENSOR_MAP_DATA_TYPE_BFLOAT16, 3, (void*)out, dims, strides, box, es, CU_TENSOR_MAP_INTERLEAVE_NONE,
           CU_TENSOR_MAP_SWIZZLE_128B, CU_TENSOR_MAP_L2_PROMOTION_NONE, CU_TENSOR_MAP_FLOAT_OOB_FILL_NONE);
  }

  cudaStream_t s = cudaStreamPerThread;
  wino_weights_kernel<<<108 / PRE_WARPS, 32 * PRE_WARPS, 0, s>>>(w, (char*)gu);

  cudaLaunchConfig_t cfg = {};
  cfg.gridDim = dim3(NCTA);
  cfg.blockDim = dim3(256);
  cfg.dynamicSmemBytes = SMEM_BYTES;
  cfg.stream = s;
  cudaLaunchAttribute attr[1];
  attr[0].id = cudaLaunchAttributeProgrammaticStreamSerialization;
  attr[0].val.programmaticStreamSerializationAllowed = 1;
  cfg.attrs = attr;
  cfg.numAttrs = 1;
  cudaLaunchKernelEx(&cfg, wino_conv_kernel, maps, b, (const char*)gu, 0u);
}
```

```cpp
#include <cuda_runtime.h>
#include <cuda_bf16.h>
#include <cuda.h>
#include <stdint.h>

#define TR_WARP 0
#ifndef EXIT_NS
#define EXIT_NS 100
#endif
#define TAILCOPY 1
#define LAZY_CLK 3400

namespace {

constexpr int IMG = 384;
constexpr int CH = 96;
constexpr int PIECE = 3072;
constexpr int GROUP = 12 * PIECE;
constexpr int NSLOT = 4;
constexpr int PLANE = 5760;
constexpr int STAGE = 2 * PLANE;
constexpr int NSTAGE = 2;
constexpr int ROWBUF = 3072;
constexpr int OFF_OUT = NSLOT * GROUP;
constexpr int OFF_IN = OFF_OUT + 12 * ROWBUF;
constexpr int OFF_BIAS = OFF_IN + 2 * NSTAGE * STAGE;
constexpr int OFF_BAR = OFF_BIAS + 1536;
constexpr int OFF_FULL = OFF_BAR;
constexpr int OFF_UFULL = OFF_BAR + 32;
constexpr int OFF_XREL = OFF_BAR + 96;
constexpr int OFF_RAW = OFF_BAR + 104;
constexpr int OFF_EMPTY = OFF_BAR + 112;
constexpr int OFF_UREL = OFF_BAR + 144;
constexpr int OFF_END = OFF_BAR + 176;
constexpr int SMEM_BYTES = OFF_END;
constexpr uint32_t SB = 0x400;
constexpr uint32_t DLO = (SB >> 4) | ((1024 >> 4) << 16);
constexpr int HALF = GROUP / 2;
constexpr int NCTA = 132;

__device__ uint4 g_U[6 * GROUP / 16 + 16];

struct Maps { CUtensorMap in, w, pf, out; uint32_t ctl[2][8][8]; };

__device__ __forceinline__ void wg_fence() { asm volatile("wgmma.fence.sync.aligned;\n" ::: "memory"); }
__device__ __forceinline__ void wg_commit() { asm volatile("wgmma.commit_group.sync.aligned;\n" ::: "memory"); }
template <int N> __device__ __forceinline__ void wg_wait() { asm volatile("wgmma.wait_group.sync.aligned %0;\n" ::"n"(N) : "memory"); }

__device__ __forceinline__ uint32_t bsub(uint32_t a, uint32_t b) {
  uint32_t r; asm("sub.rn.bf16x2 %0, %1, %2;\n" : "=r"(r) : "r"(a), "r"(b)); return r;
}
__device__ __forceinline__ uint32_t pack2(float lo, float hi) {
  uint32_t r; asm("cvt.rn.bf16x2.f32 %0, %1, %2;\n" : "=r"(r) : "f"(hi), "f"(lo)); return r;
}
__device__ __forceinline__ void mbar_init(uint32_t bar, uint32_t cnt) {
  asm volatile("mbarrier.init.shared::cta.b64 [%0], %1;\n" ::"r"(bar), "r"(cnt) : "memory");
}
__device__ __forceinline__ void mbar_wait(uint32_t bar, uint32_t parity) {
  asm volatile(
      "{\n"
      ".reg .pred p;\n"
      ".reg .u32 n;\n"
      "mov.u32 n, 0;\n"
      "LW%=:\n"
      "mbarrier.try_wait.parity.shared::cta.b64 p, [%0], %1;\n"
      "@p bra LD%=;\n"
      "add.u32 n, n, 1;\n"
      "setp.lt.u32 p, n, 1000000;\n"
      "@p bra LW%=;\n"
      "trap;\n"
      "LD%=:\n"
      "}\n" ::"r"(bar), "r"(parity) : "memory");
}
template <int N> __device__ __forceinline__ void bulk_wait_read() {
  asm volatile("cp.async.bulk.wait_group.read %0;\n" ::"n"(N) : "memory");
}
__device__ __forceinline__ uint32_t bfma(uint32_t a, uint32_t b, uint32_t c) {
  uint32_t r; asm("fma.rn.bf16x2 %0, %1, %2, %3;\n" : "=r"(r) : "r"(a), "r"(b), "r"(c)); return r;
}

template <int SCALE_D, int TB = 1>
__device__ __forceinline__ void wgmma96(float* d, uint32_t a0, uint32_t a1, uint32_t a2, uint32_t a3, uint64_t db) {
  asm volatile(
      "wgmma.mma_async.sync.aligned.m64n96k16.f32.bf16.bf16 "
      "{%0, %1, %2, %3, %4, %5, %6, %7, %8, %9, %10, %11, %12, %13, %14, %15, %16, %17, %18, %19, %20, %21, %22, %23, "
      "%24, %25, %26, %27, %28, %29, %30, %31, %32, %33, %34, %35, %36, %37, %38, %39, %40, %41, %42, %43, %44, %45, %46, %47}, "
      "{%48, %49, %50, %51}, %52, %53, 1, 1, %54;\n"
      : "+f"(d[0]), "+f"(d[1]), "+f"(d[2]), "+f"(d[3]), "+f"(d[4]), "+f"(d[5]), "+f"(d[6]), "+f"(d[7]), "+f"(d[8]), "+f"(d[9]),
        "+f"(d[10]), "+f"(d[11]), "+f"(d[12]), "+f"(d[13]), "+f"(d[14]), "+f"(d[15]), "+f"(d[16]), "+f"(d[17]), "+f"(d[18]),
        "+f"(d[19]), "+f"(d[20]), "+f"(d[21]), "+f"(d[22]), "+f"(d[23]), "+f"(d[24]), "+f"(d[25]), "+f"(d[26]), "+f"(d[27]),
        "+f"(d[28]), "+f"(d[29]), "+f"(d[30]), "+f"(d[31]), "+f"(d[32]), "+f"(d[33]), "+f"(d[34]), "+f"(d[35]), "+f"(d[36]),
        "+f"(d[37]), "+f"(d[38]), "+f"(d[39]), "+f"(d[40]), "+f"(d[41]), "+f"(d[42]), "+f"(d[43]), "+f"(d[44]), "+f"(d[45]),
        "+f"(d[46]), "+f"(d[47])
      : "r"(a0), "r"(a1), "r"(a2), "r"(a3), "l"(db), "n"(SCALE_D), "n"(TB));
}

__device__ __forceinline__ uint64_t bdesc(uint32_t lo) {
  uint64_t d;
  asm("mov.b64 %0, {%1, %2};\n" : "=l"(d) : "r"(lo), "r"((512u >> 4) | (2u << 30)));
  return d;
}

template <int N> __device__ __forceinline__ void fence_regs(float* d) {
#pragma unroll
  for (int i = 0; i < N; i++) asm volatile("" : "+f"(d[i])::"memory");
}

struct WItem { uint4 g[3]; };
__device__ __forceinline__ void witem_load(WItem& t, const __nv_bfloat16* __restrict__ w, int item, int lane) {
  const int q = item % 3, kw = (item / 3) % 3, kg = item / 9;
  const uint4* p = (const uint4*)(w + (kw * CH + kg * 8 + (lane & 7)) * CH + q * 32 + (lane >> 3) * 8);
#pragma unroll
  for (int i = 0; i < 3; i++) t.g[i] = __ldg(p + i * (3 * CH * CH / 8));
}
__device__ __forceinline__ void wino_u12(const uint4& g0, const uint4& g1, const uint4& g2, uint4& o1, uint4& o2) {
  const uint32_t* a = (const uint32_t*)&g0;
  const uint32_t* b = (const uint32_t*)&g1;
  const uint32_t* c = (const uint32_t*)&g2;
  uint32_t u1[4], u2[4];
#pragma unroll
  for (int j = 0; j < 4; j++) {
    const float sl = __uint_as_float(a[j] << 16) + __uint_as_float(c[j] << 16);
    const float sh = __uint_as_float(a[j] & 0xffff0000u) + __uint_as_float(c[j] & 0xffff0000u);
    const float bl = 0.5f * __uint_as_float(b[j] << 16), bh = 0.5f * __uint_as_float(b[j] & 0xffff0000u);
    u1[j] = pack2(fmaf(sl, 0.5f, bl), fmaf(sh, 0.5f, bh));
    u2[j] = pack2(fmaf(sl, 0.5f, -bl), fmaf(sh, 0.5f, -bh));
  }
  o1 = make_uint4(u1[0], u1[1], u1[2], u1[3]);
  o2 = make_uint4(u2[0], u2[1], u2[2], u2[3]);
}
__device__ __forceinline__ void witem_store(const WItem& t, char* dst, int item, int lane) {
  const int q = item % 3, kw = (item / 3) % 3, kg = item / 9;
  uint4 u1, u2;
  wino_u12(t.g[0], t.g[1], t.g[2], u1, u2);
  const int r = lane & 7;
  dst += (kg >> 1) * GROUP + kw * PIECE + q * 1024 + (kg & 1) * 512 + r * 64 + (((lane >> 3) ^ (r >> 1)) << 4);
  *(uint4*)(dst) = t.g[0];
  *(uint4*)(dst + 3 * PIECE) = u1;
  *(uint4*)(dst + 6 * PIECE) = u2;
  *(uint4*)(dst + 9 * PIECE) = t.g[2];
}
__global__ void __launch_bounds__(128) wino_weights_kernel(const __nv_bfloat16* __restrict__ w, char* gu) {
  WItem t;
  const int item = blockIdx.x * 4 + (threadIdx.x >> 5);
  witem_load(t, w, item, threadIdx.x & 31);
  witem_store(t, gu, item, threadIdx.x & 31);
}

struct Ctx {
  uint32_t wg;
  uint32_t warp;
  uint32_t zero;
  char* gu;
  uint32_t fused;
  uint64_t m_in, m_pf, m_out;
  int xa, ya, xb, yb;
  const uint32_t* ctl;
};

__device__ __forceinline__ void unit_xy(const Ctx& c, int step, int& x0, int& y0) {
  x0 = (step < 4) ? c.xa : c.xb;
  y0 = (step < 4) ? c.ya + 88 * step : c.yb;
}

__device__ __forceinline__ void issue_plane(uint64_t tm, uint32_t wg, int stage, int pair, uint32_t par, int x0, int y0) {
  const uint32_t bar = SB + OFF_FULL + (wg * NSTAGE + stage) * 8;
  const uint32_t dst = SB + OFF_IN + PLANE + (wg * NSTAGE + stage) * STAGE - par * PLANE;
  asm volatile(
      "{\n.reg .pred p;\n"
      "elect.sync _|p, 0xffffffff;\n"
      "@p mbarrier.arrive.expect_tx.shared::cta.b64 _, [%2], %7;\n"
      "@p cp.async.bulk.tensor.4d.shared::cluster.global.mbarrier::complete_tx::bytes [%0], [%1, {%3, %4, %5, %6}], [%2];\n"
      "}\n" ::"r"(dst), "l"(tm), "r"(bar), "r"(pair * 32), "r"(par), "r"((x0 >> 1) - par), "r"(y0 - 1), "n"(PLANE) : "memory");
}
__device__ __forceinline__ void issue_stage(uint64_t tm, uint32_t wg, int stage, int pair, int x0, int y0) {
  issue_plane(tm, wg, stage, pair, 1, x0, y0);
  issue_plane(tm, wg, stage, pair, 0, x0, y0);
}
__device__ __forceinline__ void u_reload(const char* gu, int from, int h) {
  const int hs = (from & 3) * 2 + h;
  asm volatile(
      "{\n.reg .pred p;\n"
      "elect.sync _|p, 0xffffffff;\n"
      "@p mbarrier.arrive.expect_tx.shared::cta.b64 _, [%2], %3;\n"
      "@p cp.async.bulk.shared::cluster.global.mbarrier::complete_tx::bytes [%0], [%1], %3, [%2];\n"
      "}\n" ::"r"(SB + hs * HALF), "l"(gu + ((from ^ 4) * 2 + h) * HALF), "r"(SB + OFF_UFULL + hs * 8), "n"(HALF) : "memory");
}
__device__ __forceinline__ void e_prefetch3(uint64_t tm, int c1, int c2) {
  asm volatile("{\n.reg .pred p;\nelect.sync _|p, 0xffffffff;\n"
               "@p cp.async.bulk.prefetch.tensor.3d.L2.global [%0, {%1, %2, %3}];\n}\n" ::"l"(tm), "r"(0), "r"(c1), "r"(c2) : "memory");
}
__device__ __forceinline__ void e_store3(uint64_t tm, uint32_t src, int c1, int c2) {
  asm volatile("{\n.reg .pred p;\nelect.sync _|p, 0xffffffff;\n"
               "@p cp.async.bulk.tensor.3d.global.shared::cta.bulk_group [%0, {%2, %3, %4}], [%1];\n"
               "cp.async.bulk.commit_group;\n}\n" ::"l"(tm), "r"(src), "r"(0), "r"(c1), "r"(c2) : "memory");
}
__device__ __forceinline__ void e_arrive(uint32_t bar) {
  asm volatile("{\n.reg .pred p;\nelect.sync _|p, 0xffffffff;\n@p mbarrier.arrive.shared::cta.b64 _, [%0];\n}\n" ::"r"(bar) : "memory");
}
__device__ __forceinline__ uint32_t mbar_try(uint32_t bar, uint32_t parity) {
  uint32_t ok;
  asm volatile("{\n.reg .pred p;\nmbarrier.test_wait.parity.shared::cta.b64 p, [%1], %2;\nselp.u32 %0, 1, 0, p;\n}\n"
               : "=r"(ok) : "r"(bar), "r"(parity) : "memory");
  return ok;
}

struct Addr { uint32_t e[4]; };
__device__ __forceinline__ void addr_flip(Addr& ad, uint32_t k32) {
  asm volatile("xor.b32 %0, %0, %4;\nxor.b32 %1, %1, %4;\nxor.b32 %2, %2, %4;\nxor.b32 %3, %3, %4;\n"
               : "+r"(ad.e[0]), "+r"(ad.e[1]), "+r"(ad.e[2]), "+r"(ad.e[3]) : "r"(k32));
}
template <int IMM> __device__ __forceinline__ void ldsm4(uint32_t* r, uint32_t a) {
  asm volatile("ldmatrix.sync.aligned.m8n8.x4.shared.b16 {%0,%1,%2,%3}, [%4 + %5];\n"
               : "=r"(r[0]), "=r"(r[1]), "=r"(r[2]), "=r"(r[3]) : "r"(a), "n"(IMM));
}
template <int IMM> __device__ __forceinline__ void ldsm4_tied(uint32_t* r, uint32_t a, uint32_t zero) {
  asm volatile("{\n.reg .pred p;\nsetp.ne.u32 p, %6, 0;\n@!p ldmatrix.sync.aligned.m8n8.x4.shared.b16 {%0,%1,%2,%3}, [%4 + %5];\n}\n"
               : "+r"(r[0]), "+r"(r[1]), "+r"(r[2]), "+r"(r[3]) : "r"(a), "n"(IMM), "r"(zero));
}
template <int RHO, int STG> __device__ __forceinline__ void load_row(uint32_t* d, const Addr& ad, uint32_t k32 = 32) {
  ldsm4<RHO * 576 + STG * STAGE>(d, ad.e[RHO]);
  ldsm4<RHO * 576 + 64 + STG * STAGE>(d + 4, RHO == 3 ? ad.e[0] ^ k32 : ad.e[(RHO + 1) & 3]);
}
template <int STG> __device__ __forceinline__ void load_row1_tied(uint32_t* d, const Addr& ad, uint32_t zero) {
  ldsm4_tied<576 + STG * STAGE>(d, ad.e[1], zero);
  ldsm4_tied<640 + STG * STAGE>(d + 4, ad.e[2], zero);
}
__device__ __forceinline__ uint32_t lane_id() { uint32_t l; asm volatile("mov.u32 %0, %%laneid;\n" : "=r"(l)); return l; }

template <int SCALE_D>
__device__ __forceinline__ void mma_group(float* acc, const uint32_t* v, uint32_t baddr) {
  wgmma96<SCALE_D>(acc, v[0], v[1], v[2], v[3], bdesc(baddr));
  wgmma96<1>(acc, v[4], v[5], v[6], v[7], bdesc(baddr + (2 * PIECE >> 4)));
  wgmma96<1>(acc, v[1], v[4], v[3], v[6], bdesc(baddr + (PIECE >> 4)));
  wg_commit();
}
template <uint32_t K> __device__ __forceinline__ uint32_t pinned_const(uint32_t x, uint32_t zero) {
  uint32_t m;
  asm("{\n.reg .pred p;\nsetp.ne.u32 p, %2, 0;\nselp.b32 %0, %1, %3, p;\n}\n" : "=r"(m) : "r"(x), "r"(zero), "n"(K));
  return m;
}
template <bool NEG>
__device__ __forceinline__ uint32_t pin_one(float& done, uint32_t zero) {
  asm volatile("" : "+f"(done)::"memory");
  return pinned_const<NEG ? 0xBF80BF80u : 0x3F803F80u>(__float_as_uint(done), zero);
}
__device__ __forceinline__ void vfma(uint32_t* v, const uint32_t* a, uint32_t m, const uint32_t* b) {
#pragma unroll
  for (int i = 0; i < 8; i++) v[i] = bfma(a[i], m, b[i]);
}
__device__ __forceinline__ void vsub(uint32_t* v, const uint32_t* a, const uint32_t* b) {
#pragma unroll
  for (int i = 0; i < 8; i++) v[i] = bsub(a[i], b[i]);
}
__device__ __forceinline__ uint32_t bias_frag(uint32_t lane) { return (lane & 3) ? 0u : 0x3F00u; }
__device__ __forceinline__ void mma_bias(float* acc, uint32_t a, const Ctx& c) {
  uint64_t d;
  asm("mov.b64 %0, {%1, %2};\n" : "=l"(d) : "r"((SB + OFF_BIAS) >> 4), "r"(128 >> 4));
  wgmma96<0, 0>(acc, a, a, a, a, d);
}

template <int ROW> __device__ __forceinline__ uint32_t out_buf(const Ctx& c, uint32_t dir) {
  if (ROW == 0) return SB + OFF_OUT + (4 + c.wg * 4 + c.warp) * ROWBUF;
  return (c.wg ? SB + OFF_OUT : SB + (2 + dir) * GROUP + HALF) + c.warp * ROWBUF;
}
template <int ROW>
__device__ __forceinline__ void pack_row(uint32_t (&r)[24], float (&acc)[4][48]) {
#pragma unroll
  for (int k = 0; k < 24; k++) {
    const int i = 4 * (k % 12) + 2 * (k / 12);
    if (ROW == 0) {
      acc[0][i] += acc[1][i]; acc[0][i + 1] += acc[1][i + 1];
      acc[1][i] -= acc[2][i]; acc[1][i + 1] -= acc[2][i + 1];
      acc[2][i] += acc[0][i]; acc[2][i + 1] += acc[0][i + 1];
      r[k] = pack2(acc[2][i], acc[2][i + 1]);
    } else {
      r[k] = pack2(acc[1][i] - acc[3][i], acc[1][i + 1] - acc[3][i + 1]);
    }
  }
}
template <int ROW>
__device__ __forceinline__ void stage_row(const uint32_t (&r)[24], const Ctx& c, uint32_t dir, uint32_t lane) {
  const uint32_t l3 = 48 * (lane & 7);
  const uint32_t p0 = out_buf<ROW>(c, dir) + 8 * l3 + 2 * (lane & 24);
#pragma unroll
  for (int L = 0; L < 3; L++) {
    const uint32_t a = p0 ^ ((l3 + 16 * L) & 0x70);
    asm volatile("stmatrix.sync.aligned.m8n8.x4.shared.b16 [%0], {%1,%2,%3,%4};\n" ::"r"(a + 128 * L), "r"(r[8 * L]),
                 "r"(r[8 * L + 1]), "r"(r[8 * L + 2]), "r"(r[8 * L + 3]) : "memory");
    asm volatile("stmatrix.sync.aligned.m8n8.x4.shared.b16 [%0], {%1,%2,%3,%4};\n" ::"r"((a ^ 64) + 128 * L), "r"(r[8 * L + 4]),
                 "r"(r[8 * L + 5]), "r"(r[8 * L + 6]), "r"(r[8 * L + 7]) : "memory");
  }
}
__device__ __forceinline__ void proxy_fence() { asm volatile("fence.proxy.async.shared::cta;\n" ::: "memory"); }
template <int ROW> __device__ __forceinline__ void flush_row(const Ctx& c, uint32_t dir, int x0, int y0) {
  e_store3(c.m_out, out_buf<ROW>(c, dir), (x0 * 3) >> 1, y0 + 2 * c.warp + ROW);
}
__device__ __forceinline__ void x_reload(const Ctx& c, int slot) {
  const uint32_t off = slot * GROUP + HALF + c.warp * ROWBUF;
  asm volatile(
      "{\n.reg .pred p;\n"
      "elect.sync _|p, 0xffffffff;\n"
      "@p mbarrier.arrive.expect_tx.shared::cta.b64 _, [%2], %3;\n"
      "@p cp.async.bulk.shared::cluster.global.mbarrier::complete_tx::bytes [%0], [%1], %3, [%2];\n"
      "}\n" ::"r"(SB + off), "l"(c.gu + off), "r"(SB + OFF_UFULL + (slot * 2 + 1) * 8), "n"(ROWBUF) : "memory");
}

enum : uint32_t {
  B_REFILL = 1u << 0,
  B_UREL = 1u << 3,
  B_ULOAD = 1u << 4,
  B_ST1 = 1u << 5,
  B_ST0 = 1u << 8,
  B_PF = 1u << 13,
  B_PF0 = 1u << 19,
  B_FIRST = 1u << 20,
  B_XLOAD = 1u << 21,
  B_XREL = 1u << 22,
  B_MIDWAIT = 1u << 23,
  B_NEXT = 1u << 24,
  B_EARLY = 1u << 27,
};
inline uint32_t role_mask(uint32_t wg, uint32_t warp) {
  static const int st1[4] = {0, 0, 1, 1}, st0[4] = {0, 2, 1, 2};
  static const uint32_t pf[4] = {0, 0, 0x35, 0x0A};
  uint32_t m = B_NEXT | B_FIRST | (warp == 2 ? B_PF0 : 0u);
  if (warp < 2) m |= 7u * B_REFILL;
  if (warp == 3) m |= wg ? B_ULOAD | B_XREL | B_MIDWAIT : B_UREL;
  if (wg == 0) m |= B_XLOAD | B_MIDWAIT | B_EARLY;
  else m |= B_ST1 << st1[warp];
  m |= B_ST0 << st0[warp];
  m |= pf[warp] * B_PF;
  return m;
}
inline uint32_t step_mask(int step, int nsteps) {
  uint32_t m = ~0u;
  if (step == 0) m &= ~(B_XLOAD | B_EARLY | (7u * B_ST1) | (7u * B_ST0));
  else m &= ~(B_PF0 | B_FIRST);
  if (step + 1 >= nsteps) m &= ~((6u * B_REFILL) | (7u * B_PF) | B_NEXT);
  if (step + 2 >= nsteps) m &= ~(56u * B_PF);
  return m;
}
struct Unit { int step, x0, y0, xn, yn, yp, x2, y2; uint32_t ctl; };
#define CTL(b) (u.ctl & (b))
#define TR(i)

#define LT(i)
template <int DIR, int EV>
__device__ __forceinline__ void duty_u(const Ctx& c, const Unit& u) {
  if (CTL(B_ULOAD)) { u_reload(c.gu, DIR ? 5 - (EV >> 1) : (EV >> 1), EV & 1); __syncwarp(); }
  if (CTL(B_UREL)) { e_arrive(SB + OFF_UREL + EV * 8); __syncwarp(); }
}
__device__ __forceinline__ void prefetch_piece(const Ctx& c, const Unit& u, int q) {
  const int j = q % 6;
  e_prefetch3(c.m_pf, (((q < 6 ? u.xn : u.x2) * 3) >> 1) + 12 * (j & 1), (q < 6 ? u.yn : u.y2) + 3 * (j >> 1));
}
template <int DIR, int T>
__device__ __forceinline__ void duties(const Ctx& c, const Unit& u) {
  constexpr int P = T >> 1;
  constexpr uint32_t sts = T <= 1 ? B_ST1 << T : 0u, stp = (T >= 2 && T <= 4) ? B_ST0 << (T >= 2 ? T - 2 : 0) : 0u;
  constexpr uint32_t drain = T == 1 ? B_XLOAD : T == 3 ? B_XREL : 0u;
  constexpr uint32_t mask = (B_PF << T) | ((T & 1) ? B_REFILL << P : 0u) | ((T == 1 || T == 2) ? B_UREL | B_ULOAD : 0u) | sts | stp | drain | (T == 0 ? B_EARLY : 0u);
  if (CTL(mask)) {
    if (T & 1) {
      if (CTL(B_REFILL << P)) {
        issue_plane(c.m_in, c.wg, (3 * DIR + P) & 1, (P == 2) ? 1 : (DIR ? 0 : 2), c.warp, P == 0 ? u.x0 : u.xn, P == 0 ? u.y0 : u.yn);
        __syncwarp();
      }
    }
    if (T == 0) { if (CTL(B_EARLY)) flush_row<1>(c, DIR ^ 1, c.xa, u.yp); }
    if (T == 1 || T == 2) { if (CTL(B_UREL | B_ULOAD)) duty_u<DIR, (T == 1 ? 1 : 3)>(c, u); }
    if (CTL(B_PF << T)) {
      prefetch_piece(c, u, T + 3);
      __syncwarp();
    }
    if (T == 1) { if (CTL(B_XLOAD)) { bulk_wait_read<0>(); x_reload(c, 3 - DIR); __syncwarp(); } }
    if (T == 3) { if (CTL(B_XREL)) { e_arrive(SB + OFF_XREL); __syncwarp(); } }
    if (sts) { if (CTL(sts)) flush_row<1>(c, DIR, c.xa, u.yp); }
    if (stp) { if (CTL(stp)) flush_row<0>(c, DIR, c.xa, u.yp); }
  }
}

__device__ __forceinline__ void peek_flag(uint32_t& v, const char* p, uint32_t cond) {
  asm volatile("{\n.reg .pred p;\nsetp.ne.u32 p, %2, 0;\n@p ld.relaxed.gpu.global.u32 %0, [%1];\n}\n" : "+r"(v) : "l"(p), "r"(cond) : "memory");
}
__device__ __forceinline__ void poll_flag(uint32_t& v, const char* p, uint32_t mask, uint32_t want) {
  asm volatile(
      "{\n.reg .pred p;\n.reg .u32 m, n;\nmov.u32 n, 0;\n"
      "LP%=:\n"
      "and.b32 m, %0, %2;\n"
      "setp.eq.u32 p, m, %3;\n"
      "@p bra LQ%=;\n"
      "ld.relaxed.gpu.global.u32 %0, [%1];\n"
      "add.u32 n, n, 1;\nsetp.lt.u32 p, n, 4000000;\n@p bra LP%=;\ntrap;\n"
      "LQ%=:\n"
      "fence.acquire.gpu;\n"
      "fence.proxy.async.global;\n}\n" : "+r"(v) : "l"(p), "r"(mask), "r"(want) : "memory");
}
constexpr uint32_t FLAG_ALL = 18u | (90u << 16);
__device__ __forceinline__ void late_issue(const Ctx& c) {
#pragma unroll
  for (int h = 4; h < 8; h++) u_reload(c.gu, (h >> 1) ^ 4, h & 1);
#pragma unroll
  for (int j = 0; j < 4; j++)
    asm volatile("{\n.reg .pred p;\nelect.sync _|p, 0xffffffff;\n"
                 "@p cp.async.bulk.prefetch.tensor.4d.L2.global [%0, {%1, %2, %3, %4}];\n}\n" ::"l"(c.m_in), "r"(64), "r"(j & 1),
                 "r"((c.xa >> 1) - 8 + 8 * (j >> 1) - (j & 1)), "r"(c.ya - 1) : "memory");
  __syncwarp();
}

template <int DIR>
__device__ __forceinline__ void finish(float (&acc)[4][48], const Ctx& c, const Unit& u, uint32_t lane) {
  const bool serve = DIR == 1 && c.wg == 1 && blockIdx.x >= 36;
  if (serve && c.warp == 3) {
#pragma unroll
    for (int i = 0; i < 4; i++) { mbar_wait(SB + OFF_UREL + i * 8, 0); u_reload(c.gu, i >> 1, i & 1); }
    e_arrive(SB + OFF_XREL);
  }
  {
    const uint32_t dir = DIR;
    const int x0 = u.x0, y0 = u.y0;
    if (!serve) { proxy_fence(); flush_row<0>(c, dir, x0, y0); }
    uint32_t r[24];
    pack_row<1>(r, acc);
    if (c.wg == 0) mbar_wait(SB + OFF_XREL, dir);
    stage_row<1>(r, c, dir, lane + ((u.y0 + 3) & c.zero));
    proxy_fence();
    if (!serve) flush_row<1>(c, dir, x0, y0);
  }
  LT(9);
  if (serve) {
    const int yp = c.ya + 88 * 3;
    mbar_wait(SB + OFF_UREL + 24, 0);
    __nanosleep(EXIT_NS * (3 - c.warp));
    flush_row<1>(c, 0, c.xa, yp);
    __nanosleep(EXIT_NS * 4);
    flush_row<0>(c, 0, c.xa, yp);
  }
  if (c.fused && c.wg == 1 && c.warp == 3 && lane == 0) {
    unsigned int* sync = (unsigned int*)(c.gu + 6 * GROUP);
    if (atomicAdd(sync + 32, 1u) == NCTA - 1) { sync[0] = 0; sync[32] = 0; }
  }
  bulk_wait_read<0>();
  asm volatile("exit;\n" ::: "memory");
  __builtin_unreachable();
}

template <int DIR, bool LAST>
__device__ __forceinline__ void do_unit(float (&acc)[4][48], uint32_t (&d1)[8], uint32_t (&d2)[8], uint32_t (&d3)[8], uint32_t& lane, Addr& ad,
                                        const Ctx& c, int step);
template <int DIR, int K>
__device__ __forceinline__ void second_half(float (&acc)[4][48], uint32_t (&d0)[8], uint32_t (&d1)[8], uint32_t (&d2)[8],
                                            uint32_t (&d3)[8], uint32_t lane, Addr& ad, const Ctx& c, const Unit& u) {
    constexpr int T = 5;
    constexpr int nstage = (3 * DIR + 3) & 1;
    constexpr uint32_t nub = DLO + (((DIR ? 0 : 5) & 3) * GROUP >> 4);
    uint32_t v[8], v3[8], r[24];
    (void)T;
    const uint32_t midbar = SB + OFF_XREL + c.wg * (OFF_UREL - OFF_XREL);
    const uint32_t ok = mbar_try(midbar, DIR ^ c.wg) | !CTL(B_MIDWAIT);
    vsub(v, d0, d2);
    vsub(v3, d2, d1);
    wg_fence();
    mma_group<0>(acc[0], v, nub);
    mma_group<0>(acc[2], v3, nub + (6 * PIECE >> 4));
    TR(4);
    if (!ok) mbar_wait(midbar, DIR ^ c.wg);
    load_row<3, nstage>(d3, ad, 32 + (40 + DIR + 2 * K) * c.zero);
    pack_row<1>(r, acc);
    stage_row<1>(r, c, DIR, lane + ((u.y0 + 1 + 4 * K) & c.zero));
    wg_wait<0>(); fence_regs<48>(acc[0]); fence_regs<48>(acc[2]);
}

template <int DIR, int T, bool LAST>
__device__ __forceinline__ void do_chunk(float (&acc)[4][48], uint32_t (&d1)[8], uint32_t (&d2)[8], uint32_t (&d3)[8], uint32_t& ok,
                                         uint32_t& lane, Addr& ad, const Ctx& c, const Unit& u) {
  constexpr int chunk = DIR ? 5 - T : T;
  constexpr int slot = chunk & 3;
  constexpr int kp = 3 * DIR + (T >> 1);
  constexpr int stage = kp & 1;
  constexpr int nchunk = (T == 5) ? chunk : (DIR ? chunk - 1 : chunk + 1);
  constexpr int nslot = nchunk & 3;
  constexpr int kp1 = 3 * DIR + ((T + 1) >> 1);
  constexpr int nstage = kp1 & 1;
  constexpr int ph = (chunk & 1) ^ stage, nph = (nchunk & 1) ^ nstage;
  constexpr uint32_t ub = DLO + (slot * GROUP >> 4);
  constexpr uint32_t nub = DLO + (nslot * GROUP >> 4);
  const int step = u.step;
  const uint32_t pbit = (step >> 1) & 1;
  const uint32_t wgbar = SB + c.wg * NSTAGE * 8;
  const uint32_t emptybar = wgbar + OFF_EMPTY + stage * 8;
  const uint32_t emptypar = pbit ^ ((kp >> 1) & 1);
  constexpr uint32_t h2bar = SB + OFF_UFULL + (slot * 2 + 1) * 8;
  constexpr uint32_t h1bar = SB + OFF_UFULL + (nslot * 2) * 8;
  uint32_t v[8], v1[8], v3[8], d0[8];

  if (T == 0) {
    TR(0);
    const uint32_t mp = pin_one<false>(acc[2][0], c.zero);
    vfma(v1, d1, mp, d2);
    vfma(v3, d3, pin_one<true>(acc[2][0], c.zero), d1);
    const uint32_t ba = bias_frag(lane + ((u.y0 + 2) & c.zero)) & mp;
    addr_flip(ad, 32 + (14 + DIR + 50 * LAST) * c.zero);
    wg_fence();
    load_row<2, nstage>(d2, ad);
    load_row<0, nstage>(d0, ad);
    mma_bias(acc[1], ba, c);
    mma_group<1>(acc[1], v1, ub + (3 * PIECE >> 4));
    mma_group<0>(acc[3], v3, ub + (9 * PIECE >> 4));
    TR(1);
    LT(4 + step);
    proxy_fence();
    duties<DIR, T>(c, u);
    TR(2);
    wg_wait<1>();
    if (CTL(B_UREL | B_ULOAD | (DIR == 0 ? B_FIRST : 0u))) {
      if (DIR == 0) {
        if (CTL(B_FIRST)) {
          if (CTL(B_ULOAD)) mbar_wait(SB + OFF_UREL, 0);
          mbar_wait(h1bar, 0);
        }
      }
      duty_u<DIR, 0>(c, u);
    }
    load_row1_tied<nstage>(v1, ad, c.zero);
#pragma unroll
    for (int i = 0; i < 8; i++) d1[i] = v1[i];
    TR(3);
  } else {
    wg_wait<1>();
    vfma(v1, d1, pin_one<false>(acc[3][0], c.zero), d2);
    wg_fence();
    mma_group<1>(acc[1], v1, ub + (3 * PIECE >> 4));
    TR(0);
    if (!ok) {
      if ((T & 1) && !(LAST && T == 5)) {
        if (!(LAST && T == 3)) mbar_wait(emptybar, emptypar);
        if (T < 5 || CTL(B_NEXT)) mbar_wait(wgbar + OFF_FULL + nstage * 8, pbit ^ ((kp1 >> 1) & 1));
      }
      if (T <= 2) { if (CTL(B_ULOAD)) mbar_wait(SB + OFF_UREL + (T == 1 ? 2 : 3) * 8, DIR); }
      if (T <= 2 && DIR == 0) { if (CTL(B_FIRST)) {
        mbar_wait(h2bar, 0); mbar_wait(h1bar, 0);
        if (CTL(B_PF0)) { prefetch_piece(c, u, T); if (T == 1) prefetch_piece(c, u, 0); }
        if (T == 2) asm volatile("fence.proxy.async.global;\n" ::: "memory");
      } }
      if (T == 3) mbar_wait(h2bar, pbit ^ DIR);
      if (T >= 4) mbar_wait(h2bar, DIR ^ 1);
    }
    TR(1);
    wg_wait<1>();
    if (T == 3 || T == 4) ok = mbar_try(h1bar, DIR ^ 1);
    if (LAST) {
      const uint32_t m = pin_one<true>(acc[0][0], c.zero);
      vfma(v, d1, m, d2);
      vfma(v3, d3, m, d1);
    } else {
      vsub(v, d2, d1);
      vsub(v3, d1, d3);
    }
    if (ph != nph && !(LAST && T == 5)) addr_flip(ad, 32 + (T + 6 * DIR + 1 + 50 * LAST) * c.zero);
    wg_fence();
    if (!(LAST && T == 5)) {
      load_row<2, nstage>(d2, ad);
      load_row<0, nstage>(d0, ad);
    }
    mma_group<1>(acc[2], v, ub + (6 * PIECE >> 4));
    mma_group<1>(acc[3], v3, ub + (9 * PIECE >> 4));
    if (!(LAST && T >= 3)) duties<DIR, T>(c, u);
    if (T == 5) bulk_wait_read<0>();
    TR(2);
    wg_wait<2>();
    if (T == 1) { if (CTL(B_UREL | B_ULOAD)) duty_u<DIR, 2>(c, u); }
    if (T == 3 || T == 4) { if (!ok) mbar_wait(h1bar, DIR ^ 1); }
    if (!(LAST && T == 5)) load_row1_tied<nstage>(v1, ad, c.zero);
#pragma unroll
    for (int i = 0; i < 8; i++) d1[i] = v1[i];
    TR(3);
  }
  if (T < 5) {
    {
      if (T > 0) { wg_wait<1>(); vfma(v, d2, pin_one<true>(acc[2][0], c.zero), d0); }
      else vsub(v, d0, d2);
      wg_fence();
      load_row<3, nstage>(d3, ad, 32 + (T + 6 * DIR + 20 + 50 * LAST) * c.zero);
      if (!(T & 1) && !(LAST && T > 0)) e_arrive(emptybar);
      mma_group<1>(acc[0], v, nub);
    }
    constexpr int N = T + 1;
    constexpr int kp2 = 3 * DIR + ((N + 1) >> 1);
    ok = 1;
    if (N <= 2 && DIR == 0) ok = !CTL(B_FIRST);
    if ((N & 1) && !(LAST && N == 5)) {
      if (!(LAST && N == 3)) ok &= mbar_try(emptybar, emptypar);
      ok &= mbar_try(wgbar + OFF_FULL + (kp2 & 1) * 8, pbit ^ ((kp2 >> 1) & 1)) | (N == 5 && !CTL(B_NEXT));
    }
    if (N <= 2 && !LAST) ok &= mbar_try(SB + OFF_UREL + (N == 1 ? 2 : 3) * 8, DIR) | !CTL(B_ULOAD);
    if (N == 3) ok &= mbar_try(SB + OFF_UFULL + (nslot * 2 + 1) * 8, pbit ^ DIR);
    if (N >= 4) ok &= mbar_try(SB + OFF_UFULL + (nslot * 2 + 1) * 8, DIR ^ 1);
    TR(4);
  } else {
    lane = lane_id();
    wg_wait<1>();
    fence_regs<48>(acc[0]); fence_regs<48>(acc[1]); fence_regs<48>(acc[2]);
    uint32_t r[24];
    pack_row<0>(r, acc);
    stage_row<0>(r, c, DIR, lane + (u.y0 & c.zero));
    wg_wait<0>();
    fence_regs<48>(acc[3]);
    if (LAST || !CTL(B_NEXT)) finish<DIR>(acc, c, u, lane);
    if constexpr (!LAST) {
      if constexpr (TAILCOPY && DIR == 1) if (step == 3) {
        second_half<DIR, 1>(acc, d0, d1, d2, d3, lane, ad, c, u);
        do_unit<0, true>(acc, d1, d2, d3, lane, ad, c, 4);
      }
      second_half<DIR, 0>(acc, d0, d1, d2, d3, lane, ad, c, u);
    }
  }
}

template <int DIR, bool LAST>
__device__ __forceinline__ void do_unit(float (&acc)[4][48], uint32_t (&d1)[8], uint32_t (&d2)[8], uint32_t (&d3)[8], uint32_t& lane, Addr& ad,
                                        const Ctx& c, int step) {
  Unit u;
  u.step = step;
  u.yp = c.ya + 88 * (step - 1);
  unit_xy(c, step, u.x0, u.y0);
  unit_xy(c, step + 1, u.xn, u.yn);
  unit_xy(c, step + 2, u.x2, u.y2);
  u.ctl = c.ctl[step];
  if (LAST) u.ctl &= B_REFILL | B_UREL | B_ST0 | B_XLOAD | B_EARLY | (1u << 31);
  uint32_t ok = 1;
  do_chunk<DIR, 0, LAST>(acc, d1, d2, d3, ok, lane, ad, c, u);
  do_chunk<DIR, 1, LAST>(acc, d1, d2, d3, ok, lane, ad, c, u);
  do_chunk<DIR, 2, LAST>(acc, d1, d2, d3, ok, lane, ad, c, u);
  do_chunk<DIR, 3, LAST>(acc, d1, d2, d3, ok, lane, ad, c, u);
  do_chunk<DIR, 4, LAST>(acc, d1, d2, d3, ok, lane, ad, c, u);
  do_chunk<DIR, 5, LAST>(acc, d1, d2, d3, ok, lane, ad, c, u);
}

__global__ void __launch_bounds__(256, 1)
wino_conv_kernel(const __grid_constant__ Maps maps, const __nv_bfloat16* __restrict__ w, const __nv_bfloat16* __restrict__ bias,
                 char* gu, uint32_t fused, uint32_t zero) {
  extern __shared__ __align__(1024) uint8_t smem[];
  Ctx c;
  const int tid = threadIdx.x;
  const int cta = blockIdx.x < 36 ? blockIdx.x + 96 : blockIdx.x - 36;
  const bool producer = fused && cta >= 96 && tid < 96;
  const int pidx = (cta - 96) * 3 + (tid >> 5), item = (pidx + 18) % 108;
  WItem t;
  if (producer) witem_load(t, w, item, tid & 31);
  if (tid == 32) asm volatile("prefetch.tensormap [%0];\n" ::"l"(&maps.w) : "memory");
  if (tid == 64) asm volatile("prefetch.tensormap [%0];\n" ::"l"(&maps.in) : "memory");
  const uint32_t w8 = __shfl_sync(0xffffffffu, tid >> 5, 0);
  const int lane = tid & 31;
  unsigned int* sync = (unsigned int*)(gu + 6 * GROUP);
  c.wg = w8 >> 2;
  c.warp = w8 & 3;
  c.xa = ((cta % 12) * 2 + c.wg) * 16; c.ya = (cta / 12) * 8;
  uint32_t bv = 0;
  if (w8 >= 1 && w8 <= 3) bv = ((const unsigned short*)bias)[tid - 32];
  if (cta >= 96) {
    const uint32_t t0 = clock();
    if (fused && w8 < 3) {
      witem_store(t, gu, item, lane);
      __syncwarp();
      LT(13);
      asm volatile("{\n.reg .pred p;\nelect.sync _|p, 0xffffffff;\n@p red.release.gpu.global.add.u32 [%0], %1;\n}\n" ::"l"(sync),
                   "r"(cta < 102 ? 1u : 0x10000u) : "memory");
      LT(14);
    }
    do { __nanosleep(100); } while ((uint32_t)clock() - t0 < LAZY_CLK);
  }
  if (w8 == 0) {
    if (lane == 0) {
#pragma unroll
      for (int i = 0; i < 2 * NSTAGE; i++) mbar_init(SB + OFF_FULL + i * 8, 2);
      mbar_init(SB + OFF_RAW, 1);
      asm volatile("fence.mbarrier_init.release.cluster;\n" ::: "memory");
    }
    __syncwarp();
    asm volatile(
        "{\n.reg .pred p;\n"
        "elect.sync _|p, 0xffffffff;\n"
        "@p mbarrier.arrive.expect_tx.shared::cta.b64 _, [%1], %2;\n"
        "@p cp.async.bulk.tensor.3d.shared::cluster.global.mbarrier::complete_tx::bytes [%3], [%0, {%4, %4, %4}], [%1];\n"
        "}\n" ::"l"(&maps.w), "r"(SB + OFF_RAW), "n"(9 * PIECE), "r"(SB + OFF_OUT), "r"(0) : "memory");
    issue_stage((uint64_t)&maps.in, 0, 0, 0, c.xa, c.ya);
    issue_stage((uint64_t)&maps.in, 1, 0, 0, c.xa + 16, c.ya);
  }
  c.m_in = __shfl_sync(0xffffffffu, (unsigned long long)&maps.in, 0);
  c.m_pf = __shfl_sync(0xffffffffu, (unsigned long long)&maps.pf, 0);
  c.m_out = __shfl_sync(0xffffffffu, (unsigned long long)&maps.out, 0);
  c.zero = zero;
  c.gu = gu;
  c.fused = fused;
  c.ctl = maps.ctl[cta < 96][w8];
  c.xb = (cta % 24) * 16; c.yb = 352 + (cta / 24) * 8;
  LT(0);
  if (w8 == 7) {
    if ((uint32_t)__cvta_generic_to_shared(smem) != SB) __trap();
    if (lane == 0) {
#pragma unroll
      for (int i = 0; i < 18; i++)
        if (i != 9) mbar_init(SB + OFF_UFULL + i * 8, (i == 5 || i == 7 || (i >= 10 && i < 14)) ? 4 : 1);
      asm volatile("fence.mbarrier_init.release.cluster;\n" ::: "memory");
      asm volatile("mbarrier.arrive.shared::cta.b64 _, [%0], 3;\n" ::"r"(SB + OFF_UFULL + 40) : "memory");
      asm volatile("mbarrier.arrive.shared::cta.b64 _, [%0], 3;\n" ::"r"(SB + OFF_UFULL + 56) : "memory");
      asm volatile("mbarrier.arrive.shared::cta.b64 _, [%0];\n" ::"r"(SB + OFF_UFULL) : "memory");
      asm volatile("mbarrier.arrive.shared::cta.b64 _, [%0];\n" ::"r"(SB + OFF_UFULL + 8) : "memory");
    }
  }
  Addr ad;
  {
    const int m = lane >> 3, i = lane & 7;
    const uint32_t abase = SB + OFF_IN + c.wg * NSTAGE * STAGE + (m & 1) * PLANE + (18 * c.warp + i) * 64 + (m >> 1) * 16;
#pragma unroll
    for (int s = 0; s < 4; s++) ad.e[s] = abase ^ (((abase >> 3) + 8 * s) & 0x30);
  }
  __syncthreads();
  if (w8 >= 1 && w8 <= 6) {
    const int k = (tid - 32) / 12, ng = (tid - 32) % 12;
    const uint4* q = (const uint4*)(smem + OFF_OUT) + (tid - 32);
    uint4* d = (uint4*)(smem + (ng >> 2) * 1024 + k * 64 + (((ng & 3) ^ ((k >> 1) & 3)) << 4));
    mbar_wait(SB + OFF_RAW, 0);
    if (w8 < 4) LT(12);
#pragma unroll
    for (int i = 0; i < 3; i++) {
      const uint4 g0 = q[i * 192], g1 = q[(3 + i) * 192], g2 = q[(6 + i) * 192];
      uint4 u1, u2;
      wino_u12(g0, g1, g2, u1, u2);
      d[i * 192] = g0; d[(3 + i) * 192] = u1; d[(6 + i) * 192] = u2; d[(9 + i) * 192] = g2;
    }
    if (w8 <= 3) *(uint4*)(smem + OFF_BIAS + (tid - 32) * 16) = make_uint4(bv, 0, 0, 0);
    proxy_fence();
    LT(1);
  } else if (w8 == 0) {
    mbar_wait(SB + OFF_FULL, 0);
    issue_stage(c.m_in, 0, 1, 1, c.xa, c.ya);
    issue_stage(c.m_in, 1, 1, 1, c.xa + 16, c.ya);
  }
  asm volatile("bar.arrive %0, 256;\n" ::"r"(2 - c.wg) : "memory");

  float acc[4][48];
#pragma unroll
  for (int p = 0; p < 4; p++)
#pragma unroll
    for (int i = 0; i < 48; i++) acc[p][i] = 0.f;
  uint32_t d1[8], d2[8], d3[8], ln = lane;
  {
    uint32_t d0[8], v0[8], v2[8];
    mbar_wait(SB + OFF_FULL + (c.wg * NSTAGE) * 8, 0);
    LT(2);
    uint32_t seen = FLAG_ALL;
    load_row<0, 0>(d0, ad);
    load_row<2, 0>(d2, ad);
    load_row<1, 0>(d1, ad);
    load_row<3, 0>(d3, ad);
    vsub(v0, d0, d2);
    vsub(v2, d2, d1);
    asm volatile("bar.sync %0, 256;\n" ::"r"(1 + c.wg) : "memory");
    peek_flag(seen, gu + 6 * GROUP, fused && w8 == 7);
    LT(3);
    wg_fence();
    mma_group<0>(acc[0], v0, DLO);
    mma_group<0>(acc[2], v2, DLO + (6 * PIECE >> 4));
    if (w8 == 7) {
      poll_flag(seen, gu + 6 * GROUP, 0xffffu, 18u);
      LT(11);
      u_reload(gu, 1 ^ 4, 0);
      u_reload(gu, 1 ^ 4, 1);
      poll_flag(seen, gu + 6 * GROUP, ~0u, FLAG_ALL);
      LT(12);
      late_issue(c);
    }
    wg_wait<0>(); fence_regs<48>(acc[0]); fence_regs<48>(acc[2]);
  }

#pragma unroll 1
  for (int step = 0;; step += 2) {
    do_unit<0, false>(acc, d1, d2, d3, ln, ad, c, step);
    do_unit<1, false>(acc, d1, d2, d3, ln, ad, c, step + 1);
  }
}

typedef CUresult (*EncodeFn)(CUtensorMap*, CUtensorMapDataType, cuuint32_t, void*, const cuuint64_t*, const cuuint64_t*,
                             const cuuint32_t*, const cuuint32_t*, CUtensorMapInterleave, CUtensorMapSwizzle,
                             CUtensorMapL2promotion, CUtensorMapFloatOOBfill);

}

extern "C" void kernel_launch(void* const* d_in, const int* in_sizes, int n_in, void* d_out, int out_size) {
  (void)in_sizes; (void)n_in; (void)out_size;
  const __nv_bfloat16* x = (const __nv_bfloat16*)d_in[0];
  const __nv_bfloat16* w = (const __nv_bfloat16*)d_in[1];
  const __nv_bfloat16* b = (const __nv_bfloat16*)d_in[2];
  __nv_bfloat16* out = (__nv_bfloat16*)d_out;

  static EncodeFn encode = nullptr;
  static void* gu = nullptr;
  static uint32_t fused = 0;
  if (!encode) {
    int dev = 0, sms = 0;
    cudaGetDevice(&dev);
    cudaDeviceGetAttribute(&sms, cudaDevAttrMultiProcessorCount, dev);
    fused = sms >= NCTA;
    cudaGetSymbolAddress(&gu, g_U);
    void* fn = nullptr;
    cudaDriverEntryPointQueryResult qr;
    cudaGetDriverEntryPoint("cuTensorMapEncodeTiled", &fn, cudaEnableDefault, &qr);
    encode = (EncodeFn)fn;
    cudaFuncSetAttribute(wino_conv_kernel, cudaFuncAttributeMaxDynamicSharedMemorySize, SMEM_BYTES);
  }
  Maps maps;
  for (int five = 0; five < 2; five++)
    for (int w8 = 0; w8 < 8; w8++)
      for (int st = 0; st < 8; st++)  {
        maps.ctl[five][w8][st] = role_mask(w8 >> 2, w8 & 3) & step_mask(st, (five && w8 < 4) ? 5 : 4);
        if (TAILCOPY && st == 4) maps.ctl[five][w8][st] = (maps.ctl[five][w8][st] & ~(7u * B_ST0)) | B_ST0;
      }
  {
    cuuint64_t dims[4] = {CH, 2, IMG / 2, IMG};
    cuuint64_t strides[3] = {CH * 2, 2 * CH * 2, (cuuint64_t)IMG * CH * 2};
    cuuint32_t box[4] = {32, 1, 9, 10};
    cuuint32_t es[4] = {1, 1, 1, 1};
    encode(&maps.in, CU_TENSOR_MAP_DATA_TYPE_BFLOAT16, 4, (void*)x, dims, strides, box, es, CU_TENSOR_MAP_INTERLEAVE_NONE,
           CU_TENSOR_MAP_SWIZZLE_64B, CU_TENSOR_MAP_L2_PROMOTION_NONE, CU_TENSOR_MAP_FLOAT_OOB_FILL_NONE);
  }
  {
    cuuint64_t dims[3] = {64, CH * CH / 64, 9};
    cuuint64_t strides[2] = {128, CH * CH * 2};
    cuuint32_t box[3] = {64, 24, 9};
    cuuint32_t es[3] = {1, 1, 1};
    encode(&maps.w, CU_TENSOR_MAP_DATA_TYPE_BFLOAT16, 3, (void*)w, dims, strides, box, es, CU_TENSOR_MAP_INTERLEAVE_NONE,
           CU_TENSOR_MAP_SWIZZLE_NONE, CU_TENSOR_MAP_L2_PROMOTION_NONE, CU_TENSOR_MAP_FLOAT_OOB_FILL_NONE);
  }
  {
    cuuint64_t dims[3] = {64, IMG * CH / 64, IMG};
    cuuint64_t strides[2] = {128, (cuuint64_t)IMG * CH * 2};
    cuuint32_t box[3] = {64, 12, 3};
    cuuint32_t es[3] = {1, 1, 1};
    encode(&maps.pf, CU_TENSOR_MAP_DATA_TYPE_BFLOAT16, 3, (void*)x, dims, strides, box, es, CU_TENSOR_MAP_INTERLEAVE_NONE,
           CU_TENSOR_MAP_SWIZZLE_NONE, CU_TENSOR_MAP_L2_PROMOTION_NONE, CU_TENSOR_MAP_FLOAT_OOB_FILL_NONE);
  }
  {
    cuuint64_t dims[3] = {64, IMG * CH / 64, IMG};
    cuuint64_t strides[2] = {128, (cuuint64_t)IMG * CH * 2};
    cuuint32_t box[3] = {64, 24, 1};
    cuuint32_t es[3] = {1, 1, 1};
    encode(&maps.out, CU_TENSOR_MAP_DATA_TYPE_BFLOAT16, 3, (void*)out, dims, strides, box, es, CU_TENSOR_MAP_INTERLEAVE_NONE,
           CU_TENSOR_MAP_SWIZZLE_128B, CU_TENSOR_MAP_L2_PROMOTION_NONE, CU_TENSOR_MAP_FLOAT_OOB_FILL_NONE);
  }

  cudaStream_t s = cudaStreamPerThread;
  if (!fused) wino_weights_kernel<<<27, 128, 0, s>>>(w, (char*)gu);
  wino_conv_kernel<<<NCTA, 256, SMEM_BYTES, s>>>(maps, w, b, (char*)gu, fused, 0u);
}
```
